```python
import torch

def _softmax(x, axis=-1):
    return torch.softmax(x, dim=axis)
def _gelu(x):
    return torch.nn.functional.gelu(x, approximate="tanh")
def _silu(x):
    return torch.nn.functional.silu(x)
def _sigmoid(x):
    return torch.sigmoid(x)
def _layernorm(x, axis=-1, eps=1e-5):
    m = x.mean(dim=axis, keepdim=True)
    v = x.var(dim=axis, keepdim=True, unbiased=False)
    return (x - m) / torch.sqrt(v + eps)
def _scatter_add(tgt, idx, src, axis=0):
    return tgt.clone().index_add_(axis, idx, src)
def _segment_sum(src, seg, n):
    out = torch.zeros((n,) + src.shape[1:], dtype=src.dtype)
    return out.index_add_(0, seg, src)
def _pad(x, pw):
    flat = tuple(v for pair in reversed(pw) for v in pair)
    return torch.nn.functional.pad(x, flat)

kernel_name = 'recurrent_scan__sliding_block_cached__geglu_ffn__decode'

def setup_inputs():

    _w = (lambda a: (lambda t: t.to(torch.bfloat16) if t.is_floating_point() else t)(torch.as_tensor(a)))
    def _A_setup():
        B, Sq, D = 2, 1, 448
        Hq, Hkv, Sk, Dh = 16, 8, 32768, 256
        assert Hq % Hkv == 0, (Hq, Hkv)
        return {
            "x": _w((lambda *s: torch.randn(*s, dtype=torch.bfloat16) * 0.05)(B, Sq, D)),
            "k_cache": _w((lambda *s: torch.randn(*s, dtype=torch.bfloat16) * 1.6)(B, Hkv, Sk, Dh)),
            "v_cache": _w((lambda *s: torch.randn(*s, dtype=torch.bfloat16) * 0.2)(B, Hkv, Sk, Dh)),
            "wq": _w((lambda *s: torch.randn(*s, dtype=torch.bfloat16) * 1.6)(D, Hq * Dh) * (D ** -0.5)),
            "wo": _w((lambda *s: torch.randn(*s, dtype=torch.bfloat16) * 0.2)(Hq * Dh, D) * ((Hq * Dh) ** -0.5)),
        }
    _A_in = _A_setup()

    def _B_setup():
        B, S, D, F = 2, 1, 448, 1792
        return {
            "x": _w((lambda *s: torch.randn(*s, dtype=torch.bfloat16) * 0.05)(B, S, D)),
            "w_gate": _w((lambda *s: torch.randn(*s, dtype=torch.bfloat16) * 0.1)(D, F)),
            "w_up": _w((lambda *s: torch.randn(*s, dtype=torch.bfloat16) * 0.1)(D, F)),
            "w_down": _w((lambda *s: torch.randn(*s, dtype=torch.bfloat16) * 0.1)(F, D)),
        }
    _B_in = _B_setup()

    return {
        "A_x": _A_in["x"],
        "A_k_cache": _A_in["k_cache"],
        "A_v_cache": _A_in["v_cache"],
        "A_wq": _A_in["wq"],
        "A_wo": _A_in["wo"],
        "B_x": _B_in["x"],
        "B_w_gate": _B_in["w_gate"],
        "B_w_up": _B_in["w_up"],
        "B_w_down": _B_in["w_down"],
    }

def reference(A_x, A_k_cache, A_v_cache, A_wq, A_wo, B_x, B_w_gate, B_w_up, B_w_down):
    def _A_ref(x, k_cache, v_cache, wq, wo):
        B, Sq, D = x.shape
        Hq, Dh = 16, 256
        Hkv, Sk = k_cache.shape[1], k_cache.shape[2]
        W = min(4096, max(256, Sk // 4))
        rep = Hq // Hkv
        q = (lambda x, *d: x.permute(*d))((x @ wq).reshape(B, Sq, Hq, Dh), 0, 2, 1, 3)
        k = (lambda x, n, axis: torch.repeat_interleave(x, n, dim=axis))(k_cache[:, :, Sk - W:, :], rep, axis=1)
        v = (lambda x, n, axis: torch.repeat_interleave(x, n, dim=axis))(v_cache[:, :, Sk - W:, :], rep, axis=1)
        scores = torch.einsum("bhqd,bhkd->bhqk", q, k) * (Dh ** -0.5)
        p = _softmax(scores, axis=-1)
        o = torch.einsum("bhqk,bhkd->bhqd", p, v)
        return (lambda x, *d: x.permute(*d))(o, 0, 2, 1, 3).reshape(B, Sq, Hq * Dh) @ wo

    def _B_ref(x, w_gate, w_up, w_down):
        return (_gelu(x @ w_gate) * (x @ w_up)) @ w_down

    x = A_x
    xn = _layernorm(x, axis=-1)
    s = _A_ref(xn, A_k_cache, A_v_cache, A_wq, A_wo)
    g = _silu(_B_ref(xn, B_w_gate, B_w_up, B_w_down))
    return x + s * g
```

```cpp
#include <cuda_runtime.h>
#include <cuda_bf16.h>
#include <cuda.h>
#include <stdint.h>

namespace {

constexpr int D = 448, SK = 32768, WIN = 4096, FF = 1792;
constexpr int NMAIN = 128, NHELP = 4, NCTA = NMAIN + NHELP;
#define NSLOT 9
constexpr int NS = NSLOT;
constexpr int SLOT = 16384;
constexpr int NT = 16;
#define DEPTH 3
#define FINW 0
#define GUPOS 4
#define GUT 5
#define HSLEEP 500
#define WDPF 1
#define TG 13
#define TWO 14
#define TPRE 3
#define TSTAT 6
#define WOLAST 0
#define WOPOS 22
#define VPROMO 2
#define ENDFREE 0
constexpr int NTHREADS = 288;

constexpr int OFF_RING = 0;
constexpr int OFF_W    = OFF_RING + NS * SLOT;
constexpr int OFF_P    = OFF_W + 57344;
constexpr int P_PITCH  = WIN + 8;
constexpr int OFF_XN   = OFF_P + 2 * P_PITCH * 2;
constexpr int XN_PITCH = 456;
constexpr int OFF_Q    = OFF_XN + 2 * XN_PITCH * 2;
constexpr int OFF_ZERO = OFF_Q + 1024;
constexpr int OFF_PART = OFF_ZERO + 16;
constexpr int OFF_OP   = OFF_PART + 2048;
constexpr int OFF_RED  = OFF_OP + 2048;
constexpr int OFF_TAG  = OFF_RED + 256;
constexpr int OFF_BAR  = OFF_TAG + 16;
constexpr int NBAR     = 2 * NS + 4;
constexpr int SMEM_USED = OFF_BAR + NBAR * 8;
constexpr int SMEM_BYTES = SMEM_USED + 1024;
constexpr int H_PITCH = FF + 8;
static_assert(OFF_XN % 16 == 0 && OFF_Q % 16 == 0 && OFF_P % 16 == 0 && OFF_PART % 16 == 0 && OFF_BAR % 8 == 0, "align");
static_assert(SMEM_BYTES <= 232448, "smem");

struct __align__(128) Scratch {
    uint4 sc[16 * 2048];
    uint4 s[112 * 128];
    uint4 q[NMAIN * 32];
    uint4 h[112 * 32];
    uint4 g[112 * 2];
    uint4 g3[2 * 7 * 32];
    float4 acc[2][2 * 7 * 32];
    unsigned epoch[NCTA];
};
__device__ Scratch g_scratch;

struct Params {
    const uint8_t* k;
    const uint8_t* wq_raw;
    const uint8_t* wd_raw;
    const __nv_bfloat16* x;
    __nv_bfloat16* out;
    Scratch* sx;
    alignas(64) CUtensorMap wq;
    CUtensorMap v, wg, wu, wo, wd;
};

#define STAMP(i) do {} while (0)

__device__ __forceinline__ uint32_t smem_u32(const void* p) { return (uint32_t)__cvta_generic_to_shared(p); }
__device__ __forceinline__ void mbar_init(uint32_t bar, uint32_t cnt) {
    asm volatile("mbarrier.init.shared::cta.b64 [%0], %1;" :: "r"(bar), "r"(cnt) : "memory");
}
__device__ __forceinline__ void mbar_expect_tx(uint32_t bar, uint32_t bytes) {
    asm volatile("mbarrier.arrive.expect_tx.shared::cta.b64 _, [%0], %1;" :: "r"(bar), "r"(bytes) : "memory");
}
__device__ __forceinline__ void mbar_arrive(uint32_t bar, uint32_t cnt) {
    asm volatile("mbarrier.arrive.shared::cta.b64 _, [%0], %1;" :: "r"(bar), "r"(cnt) : "memory");
}
__device__ __forceinline__ void mbar_wait(uint32_t bar, uint32_t parity) {
    uint32_t ok;
    int it = 0;
    do {
        asm volatile("{\n.reg .pred p;\nmbarrier.test_wait.parity.shared::cta.b64 p, [%1], %2;\nselp.u32 %0, 1, 0, p;\n}"
                     : "=r"(ok) : "r"(bar), "r"(parity) : "memory");
    } while (!ok && ++it < (1 << 24));
}
__device__ __forceinline__ void bulk1d(uint32_t dst, const void* src, uint32_t bytes, uint32_t bar, uint64_t pol) {
    asm volatile("cp.async.bulk.shared::cluster.global.mbarrier::complete_tx::bytes.L2::cache_hint [%0], [%1], %2, [%3], %4;"
                 :: "r"(dst), "l"(src), "r"(bytes), "r"(bar), "l"(pol) : "memory");
}
__device__ __forceinline__ void tma2d(uint32_t dst, const CUtensorMap* map, int c0, int c1, uint32_t bar) {
    asm volatile("cp.async.bulk.tensor.2d.shared::cluster.global.mbarrier::complete_tx::bytes [%0], [%1, {%3, %4}], [%2];"
                 :: "r"(dst), "l"(map), "r"(bar), "r"(c0), "r"(c1) : "memory");
}
__device__ __forceinline__ void tma2d_hint(uint32_t dst, const CUtensorMap* map, int c0, int c1, uint32_t bar, uint64_t pol) {
    asm volatile("cp.async.bulk.tensor.2d.shared::cluster.global.mbarrier::complete_tx::bytes.L2::cache_hint [%0], [%1, {%3, %4}], [%2], %5;"
                 :: "r"(dst), "l"(map), "r"(bar), "r"(c0), "r"(c1), "l"(pol) : "memory");
}
__device__ __forceinline__ void tma3d(uint32_t dst, const CUtensorMap* map, int c0, int c1, int c2, uint32_t bar) {
    asm volatile("cp.async.bulk.tensor.3d.shared::cluster.global.mbarrier::complete_tx::bytes [%0], [%1, {%3, %4, %5}], [%2];"
                 :: "r"(dst), "l"(map), "r"(bar), "r"(c0), "r"(c1), "r"(c2) : "memory");
}
__device__ __forceinline__ void ldsm4(uint32_t (&r)[4], uint32_t addr) {
    asm volatile("ldmatrix.sync.aligned.m8n8.x4.shared.b16 {%0,%1,%2,%3}, [%4];"
                 : "=r"(r[0]), "=r"(r[1]), "=r"(r[2]), "=r"(r[3]) : "r"(addr) : "memory");
}
__device__ __forceinline__ void ldsm4t(uint32_t (&r)[4], uint32_t addr) {
    asm volatile("ldmatrix.sync.aligned.m8n8.x4.trans.shared.b16 {%0,%1,%2,%3}, [%4];"
                 : "=r"(r[0]), "=r"(r[1]), "=r"(r[2]), "=r"(r[3]) : "r"(addr) : "memory");
}
__device__ __forceinline__ void lds128(uint32_t (&r)[4], uint32_t addr) {
    asm volatile("ld.shared.v4.u32 {%0,%1,%2,%3}, [%4];"
                 : "=r"(r[0]), "=r"(r[1]), "=r"(r[2]), "=r"(r[3]) : "r"(addr) : "memory");
}
__device__ __forceinline__ void mma16816(float (&c)[4], uint32_t a0, uint32_t a1, uint32_t a2, uint32_t a3, uint32_t b0, uint32_t b1) {
    asm volatile("mma.sync.aligned.m16n8k16.row.col.f32.bf16.bf16.f32 {%0,%1,%2,%3}, {%4,%5,%6,%7}, {%8,%9}, {%0,%1,%2,%3};"
                 : "+f"(c[0]), "+f"(c[1]), "+f"(c[2]), "+f"(c[3])
                 : "r"(a0), "r"(a1), "r"(a2), "r"(a3), "r"(b0), "r"(b1));
}
__device__ __forceinline__ void mma16816(float (&c)[4], const uint32_t (&a)[4], uint32_t b0, uint32_t b1) {
    mma16816(c, a[0], a[1], a[2], a[3], b0, b1);
}
__device__ __forceinline__ void bar_sync(int id, int n) { asm volatile("bar.sync %0, %1;" :: "r"(id), "r"(n) : "memory"); }
__device__ __forceinline__ void bar_arrive(int id, int n) { asm volatile("bar.arrive %0, %1;" :: "r"(id), "r"(n) : "memory"); }
__device__ __forceinline__ float bf16r(float v) { return __bfloat162float(__float2bfloat16_rn(v)); }
__device__ __forceinline__ uint32_t pack_bf16(float lo, float hi) {
    __nv_bfloat162 r = __floats2bfloat162_rn(lo, hi);
    return *reinterpret_cast<uint32_t*>(&r);
}

__device__ __forceinline__ __nv_bfloat16 geglu(float gate, float up) {
    const float ga = bf16r(gate);
    const float in = 0.7978845608028654f * (ga + 0.044715f * ga * ga * ga);
    return __float2bfloat16_rn(bf16r(0.5f * ga * (1.0f + tanhf(in))) * bf16r(up));
}

__device__ __forceinline__ void ldB(uint32_t (&r)[4], uint32_t base, int pitch_bytes, int k0, uint32_t zero, int lane) {
    const int n = lane & 7;
    ldsm4(r, n < 2 ? base + n * pitch_bytes + (k0 + 8 * (lane >> 3)) * 2 : zero);
}

__device__ __forceinline__ void pkt_store(uint4* p, float a, float b, float c, float d, uint32_t tag) {
    const uint32_t w0 = (__float_as_uint(a) & ~3u) | (tag & 3u);
    const uint32_t w1 = (__float_as_uint(b) & ~3u) | ((tag >> 2) & 3u);
    const uint32_t w2 = (__float_as_uint(c) & ~3u) | ((tag >> 4) & 3u);
    const uint32_t w3 = (__float_as_uint(d) & ~3u) | ((tag >> 6) & 3u);
    asm volatile("{\n.reg .b128 t;\n.reg .b64 lo, hi;\nmov.b64 lo, {%1, %2};\nmov.b64 hi, {%3, %4};\nmov.b128 t, {lo, hi};\n"
                 "st.relaxed.gpu.global.b128 [%0], t;\n}"
                 :: "l"(p), "r"(w0), "r"(w1), "r"(w2), "r"(w3) : "memory");
}
__device__ __forceinline__ void pkt_clear(uint4* p) { pkt_store(p, 0.f, 0.f, 0.f, 0.f, 0); }
__device__ __forceinline__ uint4 pkt_load(const uint4* p) {
    uint4 v;
    asm volatile("{\n.reg .b128 t;\n.reg .b64 lo, hi;\nld.relaxed.gpu.global.b128 t, [%4];\nmov.b128 {lo, hi}, t;\n"
                 "mov.b64 {%0, %1}, lo;\nmov.b64 {%2, %3}, hi;\n}"
                 : "=r"(v.x), "=r"(v.y), "=r"(v.z), "=r"(v.w) : "l"(p) : "memory");
    return v;
}
__device__ __forceinline__ uint32_t pkt_diff(const uint4& v, uint32_t tag) {
    return ((v.x ^ tag) | (v.y ^ (tag >> 2))) | ((v.z ^ (tag >> 4)) | (v.w ^ (tag >> 6)));
}
__device__ __forceinline__ bool pkt_ok(const uint4& v, uint32_t tag) { return (pkt_diff(v, tag) & 3u) == 0; }
__device__ __forceinline__ float pkt_f(uint32_t w) { return __uint_as_float(w & ~3u); }
constexpr int POLL_MAX = 1 << 20;
__device__ __forceinline__ uint4 pkt_poll(const uint4* p, uint32_t tag) {
    uint4 v;
    int it = 0;
    do { v = pkt_load(p); } while (!pkt_ok(v, tag) && ++it < POLL_MAX);
    return v;
}

__global__ void __launch_bounds__(NTHREADS, 1) fused_decode_kernel(const __grid_constant__ Params prm) {
    extern __shared__ uint8_t smem_raw[];
    const int tid = threadIdx.x, warp = tid >> 5, lane = tid & 31;
    const int cta = blockIdx.x;
    const bool is_main = cta < NMAIN;
    const uint32_t sb = (smem_u32(smem_raw) + 1023u) & ~1023u;
    const uint32_t bar_full = sb + OFF_BAR, bar_empty = bar_full + NS * 8;
    const uint32_t bar_wq = bar_empty + NS * 8, bar_gu = bar_wq + 8, bar_wo = bar_gu + 8, bar_wfree = bar_wo + 8;
    const int grp = cta >> 3, j = cta & 7;
    const uint8_t* const ksrc = prm.k + ((size_t)grp * SK + (SK - WIN) + j * 32) * 512;
    uint64_t pol = 0;

    if (tid == 256) {
        if (is_main) {
            asm volatile("cp.async.bulk.prefetch.L2.global [%0], %1;" :: "l"(prm.wq_raw + cta * 28672), "r"(28672) : "memory");
            asm volatile("createpolicy.fractional.L2::evict_first.b64 %0, 1.0;" : "=l"(pol));
#pragma unroll
            for (int i = 0; i < DEPTH - 1; i++) mbar_init(bar_full + i * 8, 1);
            mbar_init(bar_wq, 1);
            asm volatile("fence.mbarrier_init.release.cluster;" ::: "memory");
            mbar_expect_tx(bar_wq, 28672);
            tma2d(sb + OFF_W, &prm.wq, ((grp & 7) * 8 + (grp >> 3) * 4 + (j >> 1)) * 64, (j & 1) * 224, bar_wq);
#pragma unroll
            for (int i = 0; i < DEPTH - 1; i++) {
                mbar_expect_tx(bar_full + i * 8, SLOT);
                bulk1d(sb + OFF_RING + i * SLOT, ksrc + (size_t)i * 256 * 512, SLOT, bar_full + i * 8, pol);
            }
#pragma unroll
            for (int i = DEPTH - 1; i < NS; i++) mbar_init(bar_full + i * 8, 1);
        } else {
#pragma unroll
            for (int i = 0; i < NS; i++) mbar_init(bar_full + i * 8, 1);
        }
#pragma unroll
        for (int i = 0; i < NS; i++) mbar_init(bar_empty + i * 8, 8);
        mbar_init(bar_gu, 1); mbar_init(bar_wo, 1); mbar_init(bar_wfree, 8);
        asm volatile("fence.mbarrier_init.release.cluster;" ::: "memory");
    }

    uint8_t* sm = smem_raw + (sb - smem_u32(smem_raw));
    Scratch* const sx = prm.sx;
    const int b = grp >> 3;
    const bool has_ffn = is_main && j < 7;
    const int fblk = grp * 7 + j;
    const int qblk = (grp & 7) * 16 + b * 8 + j;
    const uint32_t zero = sb + OFF_ZERO;
    volatile uint32_t* s_tag = reinterpret_cast<volatile uint32_t*>(sm + OFF_TAG);
    float* s_part = reinterpret_cast<float*>(sm + OFF_PART);
    float* s_red = reinterpret_cast<float*>(sm + OFF_RED);
    const int ncg = is_main ? 0 : (cta - NMAIN < 3 ? 2 : 1);
    const int cg0 = (cta - NMAIN) * 2;

    uint32_t xw[7];
    if (warp < 2 && is_main) {
        const uint32_t* xp = reinterpret_cast<const uint32_t*>(prm.x + warp * D);
#pragma unroll
        for (int i = 0; i < 7; i++) xw[i] = __ldg(xp + lane + 32 * i);
    }
    unsigned epoch = 0;
    if (tid == 64) epoch = sx->epoch[cta];
    if (tid == 96) *reinterpret_cast<uint4*>(sm + OFF_ZERO) = make_uint4(0, 0, 0, 0);
    if (is_main) {
        if (warp == 2) pkt_clear(&sx->q[qblk * 32 + lane]);
        if (warp == 3 && has_ffn) pkt_clear(&sx->h[fblk * 32 + lane]);
    } else if (FINW == 0) {
        if (tid < ncg * 64) pkt_clear(&sx->g3[(((tid >> 5) & 1) * 7 + cg0 + (tid >> 6)) * 32 + lane]);
    } else if (tid < ncg * 32) {
        pkt_clear(&sx->g[(((tid >> 4) & 1) * 56 + (cg0 + (tid >> 5)) * 8 + ((tid >> 1) & 7)) * 2 + (tid & 1)]);
    }
    __syncthreads();

    if (warp == 8) {
        if (lane == 0) {
            if (is_main) {
                asm volatile("prefetch.tensormap [%0];" :: "l"(&prm.wg) : "memory");
                asm volatile("prefetch.tensormap [%0];" :: "l"(&prm.wu) : "memory");
                asm volatile("prefetch.tensormap [%0];" :: "l"(&prm.v) : "memory");
                asm volatile("prefetch.tensormap [%0];" :: "l"(&prm.wo) : "memory");
                const int vrow = grp * SK + (SK - WIN);
                int slot = DEPTH - 1, ph = 1, lslot = 0, lph = 0;
                for (int n = DEPTH - 1; n < 2 * NT; n++) {
                    if (n == DEPTH - 1) mbar_wait(bar_wq, 0);
                    if (n == GUPOS && has_ffn) {
                        mbar_expect_tx(bar_gu, 28672);
                        tma2d(sb + OFF_W + 28672, (fblk & 1) ? &prm.wu : &prm.wg, (fblk >> 2) * 64, ((fblk >> 1) & 1) * 224, bar_gu);
                    }
                    if (n >= NS) mbar_wait(bar_empty + slot * 8, ph);
                    if (n >= DEPTH && n < 2 * NT - ENDFREE) {
                        mbar_wait(bar_full + lslot * 8, lph);
                        if (++lslot == NS) { lslot = 0; lph ^= 1; }
                    }
                    const uint32_t bar = bar_full + slot * 8, dst = sb + OFF_RING + slot * SLOT;
                    mbar_expect_tx(bar, SLOT);
                    if (n < NT) bulk1d(dst, ksrc + (size_t)n * 256 * 512, SLOT, bar, pol);
                    else        tma2d_hint(dst, &prm.v, j * 32, vrow + (n - NT) * 256, bar, pol);
                    if (++slot == NS) { slot = 0; ph ^= 1; }
                    if (n == WOPOS) { mbar_wait(bar_wfree, 0); mbar_expect_tx(bar_wo, 57344); }
                    if (n >= WOPOS && n < WOPOS + 7 - WOLAST) {
                        tma3d(sb + OFF_W + (n - WOPOS) * 8192, &prm.wo, (n - WOPOS) * 64, j * 32, (grp & 7) * 2, bar_wo);
                    }
                }
                for (int c = 7 - WOLAST; c < 7; c++) tma3d(sb + OFF_W + c * 8192, &prm.wo, c * 64, j * 32, (grp & 7) * 2, bar_wo);
                STAMP(1);
            } else {
                int slot = 0, ph = 1;
                for (int n = 0; n < 14 * ncg; n++) {
                    if (n >= NS) mbar_wait(bar_empty + slot * 8, ph);
                    const uint32_t bar = bar_full + slot * 8;
                    mbar_expect_tx(bar, SLOT);
                    tma2d(sb + OFF_RING + slot * SLOT, &prm.wd, (cg0 + (ncg == 2 ? (n & 1) : 0)) * 64, (ncg == 2 ? (n >> 1) : n) * 128, bar);
                    if (n < NS && WDPF) {
                        if (n >= 2) mbar_wait(bar_full + (n - 2) * 8, 0);
                        if (n >= 1) asm volatile("cp.async.bulk.prefetch.L2.global [%0], %1;"
                                     :: "l"(prm.wd_raw + (size_t)(512 + (cta - NMAIN) * 320 + (n - 1) * 40) * 896), "r"(40 * 896) : "memory");
                    }
                    if (++slot == NS) { slot = 0; ph ^= 1; }
                }
            }
        }
        __syncwarp();
        if (cta < 14) sx->acc[(s_tag[1] + 1) & 1][cta * 32 + lane] = make_float4(0.f, 0.f, 0.f, 0.f);
        return;
        if (!has_ffn) return;
        const uint32_t tag = *s_tag;
        const int r = fblk - b * 56;
        const int col = (r >> 3) * 64 + (r & 7) + 32 * (lane & 1) + 8 * ((lane >> 1) & 3);
        const float xv = __bfloat162float(prm.x[b * D + col]);
        const uint4 gv = pkt_poll(&sx->g[fblk * 2 + (lane & 1)], tag);
        const bool hi = lane & 4, lo = lane & 2;
        const float g = pkt_f(hi ? (lo ? gv.w : gv.z) : (lo ? gv.y : gv.x));
        bar_sync(3, 160);
        float f0 = s_red[lane];
        f0 += __shfl_xor_sync(~0u, f0, 8);
        f0 += __shfl_xor_sync(~0u, f0, 16);
        if (lane < 8) prm.out[b * D + col] = __float2bfloat16_rn(xv + bf16r(bf16r(f0) * g));
        if (lane == 0) STAMP(9);
        return;
    }

    if (!is_main) {
        if (tid == 64) { sx->epoch[cta] = epoch + 1; *s_tag = epoch % 255u + 1u; }
        bar_sync(1, 256);
        const uint32_t tag = *s_tag;
        __nv_bfloat16* h_s = reinterpret_cast<__nv_bfloat16*>(sm + OFF_W);
        {
            uint4 v[4][4];
            const int ncb = warp < 4 ? 4 : 3;
            int it = 0;
            uint32_t bad;
            do {
                if (it) __nanosleep(HSLEEP);
                bad = 0;
#pragma unroll
                for (int i = 0; i < 4; i++)
#pragma unroll
                    for (int q = 0; q < 4; q++)
                        if (i < ncb) v[i][q] = pkt_load(&sx->h[(warp + 8 * i) * 128 + q * 32 + lane]);
#pragma unroll
                for (int i = 0; i < 4; i++)
                    if (i < ncb) bad |= (pkt_diff(v[i][0], tag) | pkt_diff(v[i][1], tag)) | (pkt_diff(v[i][2], tag) | pkt_diff(v[i][3], tag));
            } while ((bad & 3u) && ++it < POLL_MAX);
#pragma unroll
            for (int i = 0; i < 4; i++) {
                if (i < ncb) {
                    __nv_bfloat16* dst = h_s + (warp + 8 * i) * 64 + (lane >> 3) * 16 + (lane & 7);
                    dst[0]           = geglu(pkt_f(v[i][0].x) + pkt_f(v[i][2].x), pkt_f(v[i][1].x) + pkt_f(v[i][3].x));
                    dst[H_PITCH]     = geglu(pkt_f(v[i][0].y) + pkt_f(v[i][2].y), pkt_f(v[i][1].y) + pkt_f(v[i][3].y));
                    dst[8]           = geglu(pkt_f(v[i][0].z) + pkt_f(v[i][2].z), pkt_f(v[i][1].z) + pkt_f(v[i][3].z));
                    dst[H_PITCH + 8] = geglu(pkt_f(v[i][0].w) + pkt_f(v[i][2].w), pkt_f(v[i][1].w) + pkt_f(v[i][3].w));
                }
            }
        }
        bar_sync(1, 256);
        if (tid == 0) STAMP(10);
        const int mt = warp & 3, kh = warp >> 2;
        float acc[2][4] = {};
        int slot = 0, ph = 0;
        for (int rb = 0; rb < 14; rb++) {
            uint32_t bf[2][4];
            ldB(bf[0], sb + OFF_W, H_PITCH * 2, rb * 128 + kh * 64, zero, lane);
            ldB(bf[1], sb + OFF_W, H_PITCH * 2, rb * 128 + kh * 64 + 32, zero, lane);
#pragma unroll
            for (int ci = 0; ci < 2; ci++) {
                if (ci < ncg) {
                    mbar_wait(bar_full + slot * 8, ph);
                    const uint32_t base = sb + OFF_RING + slot * SLOT;
#pragma unroll
                    for (int ks = 0; ks < 4; ks++) {
                        const int row = kh * 64 + ks * 16 + (lane & 7) + 8 * (lane >> 4);
                        const int ch = 2 * mt + ((lane >> 3) & 1);
                        uint32_t a[4];
                        ldsm4t(a, base + row * 128 + ((ch ^ (row & 7)) << 4));
                        mma16816(acc[ci], a, bf[ks >> 1][(ks & 1) * 2], bf[ks >> 1][(ks & 1) * 2 + 1]);
                    }
                    __syncwarp();
                    if (lane == 0) mbar_arrive(bar_empty + slot * 8, 1);
                    if (++slot == NS) { slot = 0; ph ^= 1; }
                }
            }
        }
        if ((lane & 3) == 0) {
#pragma unroll
            for (int ci = 0; ci < 2; ci++) {
                float* p = s_part + kh * 256 + ci * 128 + (mt * 16 + (lane >> 2)) * 2;
                p[0] = acc[ci][0]; p[1] = acc[ci][1]; p[16] = acc[ci][2]; p[17] = acc[ci][3];
            }
        }
        bar_sync(1, 256);
        if (tid < ncg * 64) {
            const int ci = tid >> 6, bb = (tid >> 5) & 1, gq = lane >> 2, t4 = lane & 3;
            float g[3];
#pragma unroll
            for (int i = 0; i < 3; i++) {
                const int col = (gq + 8 * (3 * t4 + i)) & 63;
                const float y = bf16r(s_part[ci * 128 + col * 2 + bb] + s_part[256 + ci * 128 + col * 2 + bb]);
                g[i] = bf16r(y / (1.0f + expf(-y)));
            }
            pkt_store(&sx->g3[(bb * 7 + cg0 + ci) * 32 + lane], g[0], g[1], g[2], 0.f, tag);
        }
        if (false) {
            const int ci = tid >> 5, bb = (tid >> 4) & 1, gq = (tid >> 1) & 7, k = tid & 1;
            float g[4];
#pragma unroll
            for (int i = 0; i < 4; i++) {
                const int col = gq + 8 * i + 32 * k;
                const float y = bf16r(s_part[ci * 128 + col * 2 + bb] + s_part[256 + ci * 128 + col * 2 + bb]);
                g[i] = bf16r(y / (1.0f + expf(-y)));
            }
            pkt_store(&sx->g[(bb * 56 + (cg0 + ci) * 8 + gq) * 2 + k], g[0], g[1], g[2], g[3], tag);
        }
        if (tid == 0) STAMP(11);
        return;
    }

    if (warp < 2) {
        float xv[14], sum = 0.f;
#pragma unroll
        for (int i = 0; i < 7; i++) {
            xv[2 * i] = __uint_as_float(xw[i] << 16);
            xv[2 * i + 1] = __uint_as_float(xw[i] & 0xffff0000u);
            sum += xv[2 * i] + xv[2 * i + 1];
        }
#pragma unroll
        for (int o = 16; o; o >>= 1) sum += __shfl_xor_sync(~0u, sum, o);
        const float mean = sum * (1.0f / D);
        float var = 0.f;
#pragma unroll
        for (int i = 0; i < 14; i++) { const float d = xv[i] - mean; var += d * d; }
#pragma unroll
        for (int o = 16; o; o >>= 1) var += __shfl_xor_sync(~0u, var, o);
        const float mb = bf16r(mean);
        const float sd = bf16r(sqrtf(bf16r(bf16r(var * (1.0f / D)) + 1e-5f)));
        uint32_t* xn = reinterpret_cast<uint32_t*>(sm + OFF_XN + warp * XN_PITCH * 2);
#pragma unroll
        for (int i = 0; i < 7; i++) xn[lane + 32 * i] = pack_bf16(bf16r(xv[2 * i] - mb) / sd, bf16r(xv[2 * i + 1] - mb) / sd);
    }
    if (tid == 64) { sx->epoch[cta] = epoch + 1; *s_tag = epoch % 255u + 1u; s_tag[1] = epoch; }
    bar_sync(1, 256);
    const uint32_t tag = *s_tag;

    auto project = [&](uint32_t wbase, int khalf, uint32_t bar, uint4* dst) {
        uint32_t xb[7][4];
#pragma unroll
        for (int i = 0; i < 7; i++) ldB(xb[i], sb + OFF_XN, XN_PITCH * 2, khalf * 224 + i * 32, zero, lane);
        float acc[2][4] = {};
        mbar_wait(bar, 0);
#pragma unroll
        for (int ks = 0; ks < 14; ks++) {
            const int row = ks * 16 + (lane & 7) + 8 * (lane >> 4);
            const int ch = 2 * (warp & 3) + ((lane >> 3) & 1);
            uint32_t a[4];
            ldsm4t(a, wbase + row * 128 + ((ch ^ (row & 7)) << 4));
            mma16816(acc[ks & 1], a, xb[ks >> 1][(ks & 1) * 2], xb[ks >> 1][(ks & 1) * 2 + 1]);
        }
        if ((lane & 3) == 0)
            pkt_store(dst + (warp & 3) * 8 + (lane >> 2), acc[0][0] + acc[1][0], acc[0][1] + acc[1][1], acc[0][2] + acc[1][2], acc[0][3] + acc[1][3], tag);
        __syncwarp();
        if (lane == 0) mbar_arrive(bar_wfree, 1);
    };
    if (warp < 4) project(sb + OFF_W, j & 1, bar_wq, &sx->q[qblk * 32]);
    else {
        if (!has_ffn && lane == 0) mbar_arrive(bar_wfree, 1);
        mbar_wait(bar_wq, 0);
    }
    if (tid == 0) STAMP(2);
    {
        const uint4* src = &sx->q[((grp & 7) * 8 + warp) * 64 + lane];
        uint4 u, v;
        int it = 0;
        do { u = pkt_load(src); v = pkt_load(src + 32); } while (((pkt_diff(u, tag) | pkt_diff(v, tag)) & 3u) && ++it < POLL_MAX);
        __nv_bfloat16* dst = reinterpret_cast<__nv_bfloat16*>(sm + OFF_Q) + warp * 64 + (lane >> 3) * 16 + (lane & 7);
        dst[0] = __float2bfloat16_rn(pkt_f(b ? u.y : u.x) + pkt_f(b ? v.y : v.x));
        dst[8] = __float2bfloat16_rn(pkt_f(b ? u.w : u.z) + pkt_f(b ? v.w : v.z));
    }
    bar_sync(1, 256);
    if (tid == 0) STAMP(3);

    const int pidx = ((lane >> 4) * 8 + warp) * 16 + (lane & 15);
    const uint4* const sc_src = &sx->sc[grp * 2048 + pidx];
    uint4 sv[4];
    {
        const int g = lane >> 2, t4 = lane & 3;
        uint32_t qb[8][4];
#pragma unroll
        for (int i = 0; i < 8; i++) lds128(qb[i], sb + OFF_Q + (g & 1) * 512 + ((i ^ ((g >> 1) & 1)) * 32 + t4 * 8) * 2);
        const int mt = warp & 1;
        const uint32_t roff = (mt * 16 + 2 * g) * 512 + t4 * 16;
        for (int t = 0; t < NT; t++) {
            const int slot = t % NS;
            if ((slot & 3) != (warp >> 1)) continue;
            if (t >= GUT && t < GUT + 4 && warp >= 4 && has_ffn) project(sb + OFF_W + 28672, (fblk >> 1) & 1, bar_gu, &sx->h[fblk * 32]);
            if (t >= NT - 4) {
#pragma unroll
                for (int i = 0; i < 4; i++) sv[i] = pkt_load(sc_src + i * 256);
            }
            mbar_wait(bar_full + slot * 8, (t / NS) & 1);
            const uint32_t base = sb + OFF_RING + slot * SLOT + roff;
            float acc0[4] = {}, acc1[4] = {};
#pragma unroll
            for (int i = 0; i < 8; i++) {
                uint32_t r0[4], r1[4];
                const uint32_t a = base + ((i ^ (g & 1)) << 6);
                lds128(r0, a);
                lds128(r1, a + 512);
                mma16816(acc0, r0[0], r1[0], r0[1], r1[1], qb[i][0], qb[i][1]);
                mma16816(acc1, r0[2], r1[2], r0[3], r1[3], qb[i][2], qb[i][3]);
            }
            __syncwarp();
            if (lane == 0) mbar_arrive(bar_empty + slot * 8, 4);
            if (t4 == (g & 1)) {
                pkt_store(&sx->sc[grp * 2048 + ((t * 8 + j) * 2 + mt) * 8 + g],
                          bf16r(acc0[0] + acc1[0]) * 0.0625f, bf16r(acc0[2] + acc1[2]) * 0.0625f,
                          bf16r(acc0[1] + acc1[1]) * 0.0625f, bf16r(acc0[3] + acc1[3]) * 0.0625f, tag);
            }
        }
    }
    if (tid == 0) STAMP(4);

    uint4* const s_dst = &sx->s[((b * 56 + warp * 8 + (lane >> 2)) * 64 + (cta & 63)) * 2 + (lane & 1)];
    if (FINW && warp < 7 && (lane & 2) == 0) pkt_clear(s_dst);
    float oacc[2][4] = {};
    uint32_t wa[4][4][4];
    const int ocol = b * D + warp * 64 + (lane >> 2) + 24 * ((lane & 3) < 3 ? (lane & 3) : 0);
    const uint4* const g_src = &sx->g3[(b * 7 + warp) * 32 + lane];
    uint4 gv;
    __nv_bfloat16 xq[3];
    const int chb = (lane >> 3) & 1;
    {
        const float L2E = 1.4426950408889634f;
        uint32_t* const p0 = reinterpret_cast<uint32_t*>(sm + OFF_P) + pidx;
        uint32_t* const p1 = reinterpret_cast<uint32_t*>(sm + OFF_P + P_PITCH * 2) + pidx;
        float m0 = -INFINITY, m1 = -INFINITY, l0 = 0.f, l1 = 0.f, f0 = 1.f, f1 = 1.f;
        int slot = NT % NS, ph = (NT / NS) & 1;
        const int rowl = warp * 32 + (lane & 7) + 8 * (lane >> 4);
#pragma unroll 1
        for (int t = 0; t < NT / 2; t++) {
            if (t == TSTAT - TPRE) {
#pragma unroll
                for (int i = 0; i < 4; i++) sv[i] = pkt_load(sc_src + (4 + i) * 256);
            }
            if (t == 0 || t == TSTAT) {
                const int i0 = t ? 4 : 0;
                int it = 0;
                while ((((pkt_diff(sv[0], tag) | pkt_diff(sv[1], tag)) | (pkt_diff(sv[2], tag) | pkt_diff(sv[3], tag))) & 3u) && ++it < POLL_MAX) {
#pragma unroll
                    for (int i = 0; i < 4; i++) sv[i] = pkt_load(sc_src + (i0 + i) * 256);
                }
                float e[4][4];
                float n0 = m0, n1 = m1;
#pragma unroll
                for (int i = 0; i < 4; i++) {
                    e[i][0] = pkt_f(sv[i].x); e[i][1] = pkt_f(sv[i].y); e[i][2] = pkt_f(sv[i].z); e[i][3] = pkt_f(sv[i].w);
                    n0 = fmaxf(n0, fmaxf(e[i][0], e[i][1])); n1 = fmaxf(n1, fmaxf(e[i][2], e[i][3]));
                }
#pragma unroll
                for (int o = 16; o; o >>= 1) {
                    n0 = fmaxf(n0, __shfl_xor_sync(~0u, n0, o));
                    n1 = fmaxf(n1, __shfl_xor_sync(~0u, n1, o));
                }
                l0 *= exp2f((m0 - n0) * L2E); l1 *= exp2f((m1 - n1) * L2E);
#pragma unroll
                for (int i = 0; i < 4; i++) {
                    e[i][0] = exp2f((e[i][0] - n0) * L2E); e[i][1] = exp2f((e[i][1] - n0) * L2E);
                    e[i][2] = exp2f((e[i][2] - n1) * L2E); e[i][3] = exp2f((e[i][3] - n1) * L2E);
                    l0 += e[i][0] + e[i][1]; l1 += e[i][2] + e[i][3];
                }
                float c0 = 1.f, c1 = 1.f;
                if (t) {
#pragma unroll
                    for (int o = 16; o; o >>= 1) {
                        l0 += __shfl_xor_sync(~0u, l0, o);
                        l1 += __shfl_xor_sync(~0u, l1, o);
                    }
                    if (lane == 0) *reinterpret_cast<float4*>(s_red + 32 + warp * 4) = make_float4(n0, l0, n1, l1);
                    bar_sync(1, 256);
                    const float4 st = *reinterpret_cast<const float4*>(s_red + 32 + (lane & 7) * 4);
                    float M0 = st.x, M1 = st.z;
#pragma unroll
                    for (int o = 4; o; o >>= 1) {
                        M0 = fmaxf(M0, __shfl_xor_sync(~0u, M0, o));
                        M1 = fmaxf(M1, __shfl_xor_sync(~0u, M1, o));
                    }
                    float L0 = st.y * exp2f((st.x - M0) * L2E), L1 = st.w * exp2f((st.z - M1) * L2E);
#pragma unroll
                    for (int o = 4; o; o >>= 1) {
                        L0 += __shfl_xor_sync(~0u, L0, o);
                        L1 += __shfl_xor_sync(~0u, L1, o);
                    }
                    c0 = exp2f((n0 - M0) * L2E) / L0; c1 = exp2f((n1 - M1) * L2E) / L1;
                    f0 = exp2f((m0 - M0) * L2E) / L0; f1 = exp2f((m1 - M1) * L2E) / L1;
                }
                m0 = n0; m1 = n1;
#pragma unroll
                for (int i = 0; i < 4; i++) {
                    p0[(i0 + i) * 256] = pack_bf16(e[i][0] * c0, e[i][1] * c0);
                    p1[(i0 + i) * 256] = pack_bf16(e[i][2] * c1, e[i][3] * c1);
                }
                __syncwarp();
                if (tid == 0) STAMP(t ? 15 : 14);
            }
            uint32_t pb[4];
            ldB(pb, sb + OFF_P, P_PITCH * 2, t * 256 + warp * 32, zero, lane);
            mbar_wait(bar_full + slot * 8, ph);
            const uint32_t base = sb + OFF_RING + slot * SLOT;
#pragma unroll
            for (int ks = 0; ks < 2; ks++) {
                const int row = ks * 16 + rowl;
#pragma unroll
                for (int mt = 0; mt < 2; mt++) {
                    uint32_t a[4];
                    ldsm4t(a, base + row * 64 + (((2 * mt + chb) ^ ((row >> 1) & 3)) << 4));
                    mma16816(oacc[mt], a, pb[ks * 2], pb[ks * 2 + 1]);
                }
            }
            __syncwarp();
            if (lane == 0) mbar_arrive(bar_empty + slot * 8, 1);
            if (++slot == NS) { slot = 0; ph ^= 1; }
        }
        static_assert(NS >= NT / 2, "ring");
        float oacc2[2][4] = {};
        uint32_t pb[NT / 2][4];
#pragma unroll
        for (int t = NT / 2; t < NT; t++) ldB(pb[t - NT / 2], sb + OFF_P, P_PITCH * 2, t * 256 + warp * 32, zero, lane);
#pragma unroll
        for (int mt = 0; mt < 2; mt++) { oacc[mt][0] *= f0; oacc[mt][1] *= f1; oacc[mt][2] *= f0; oacc[mt][3] *= f1; }
#pragma unroll
        for (int t = NT / 2; t < NT; t++) {
            if (t == TG && warp < 7) {
                gv = pkt_load(g_src);
                const __nv_bfloat16* xp = prm.x + ocol;
                xq[0] = xp[0]; xq[1] = xp[8]; xq[2] = xp[(lane & 3) < 2 ? 16 : 0];
            }
            if (!WOLAST && t == TWO && warp < 7) {
                mbar_wait(bar_wo, 0);
#pragma unroll
                for (int mt = 0; mt < 4; mt++)
#pragma unroll
                    for (int ks = 0; ks < 4; ks++) {
                        const int row = ks * 16 + (lane & 7) + 8 * (lane >> 4);
                        ldsm4t(wa[mt][ks], sb + OFF_W + warp * 8192 + row * 128 + (((2 * mt + chb) ^ (row & 7)) << 4));
                    }
            }
            mbar_wait(bar_full + ((NT + t) % NS) * 8, ((NT + t) / NS) & 1);
            const uint32_t base = sb + OFF_RING + ((NT + t) % NS) * SLOT + rowl * 64;
            uint32_t a[2][2][4];
#pragma unroll
            for (int ks = 0; ks < 2; ks++)
#pragma unroll
                for (int mt = 0; mt < 2; mt++) ldsm4t(a[ks][mt], base + ks * 1024 + (((2 * mt + chb) ^ ((rowl >> 1) & 3)) << 4));
#pragma unroll
            for (int mt = 0; mt < 2; mt++) {
                mma16816(oacc[mt], a[0][mt], pb[t - NT / 2][0], pb[t - NT / 2][1]);
                mma16816(oacc2[mt], a[1][mt], pb[t - NT / 2][2], pb[t - NT / 2][3]);
            }
        }
#pragma unroll
        for (int mt = 0; mt < 2; mt++)
#pragma unroll
            for (int i = 0; i < 4; i++) oacc[mt][i] += oacc2[mt][i];
    }
    if (tid == 0) STAMP(5);
    if ((lane & 3) == 0) {
        float* p = reinterpret_cast<float*>(sm + OFF_OP) + warp * 64 + (lane >> 2);
        p[0] = oacc[0][0]; p[8] = oacc[0][2]; p[16] = oacc[1][0]; p[24] = oacc[1][2];
        p[32] = oacc[0][1]; p[40] = oacc[0][3]; p[48] = oacc[1][1]; p[56] = oacc[1][3];
    }
    if (warp == 7) {
        bar_arrive(2, 256);
    } else {
        bar_sync(2, 256);
        if (tid == 0) STAMP(7);
        const float2* pp = reinterpret_cast<const float2*>(sm + OFF_OP) + lane;
        float2 v[8];
#pragma unroll
        for (int w = 0; w < 8; w++) v[w] = pp[w * 32];
        const uint32_t ow = pack_bf16(((v[0].x + v[1].x) + (v[2].x + v[3].x)) + ((v[4].x + v[5].x) + (v[6].x + v[7].x)),
                                      ((v[0].y + v[1].y) + (v[2].y + v[3].y)) + ((v[4].y + v[5].y) + (v[6].y + v[7].y)));
        if (WOLAST) {
            mbar_wait(bar_wo, 0);
#pragma unroll
            for (int ks = 0; ks < 4; ks++)
#pragma unroll
                for (int mt = 0; mt < 4; mt++) {
                    const int row = ks * 16 + (lane & 7) + 8 * (lane >> 4);
                    ldsm4t(wa[mt][ks], sb + OFF_W + warp * 8192 + row * 128 + (((2 * mt + chb) ^ (row & 7)) << 4));
                }
        }
        float acc[2][4][4] = {};
#pragma unroll
        for (int ks = 0; ks < 4; ks++) {
            const uint32_t b0 = __shfl_sync(~0u, ow, ks * 8 + (lane & 3));
            const uint32_t b1 = __shfl_sync(~0u, ow, ks * 8 + 4 + (lane & 3));
#pragma unroll
            for (int mt = 0; mt < 4; mt++) mma16816(acc[ks & 1][mt], wa[mt][ks], b0, b1);
        }
        {
            float v[8];
#pragma unroll
            for (int mt = 0; mt < 4; mt++) { v[2 * mt] = acc[0][mt][0] + acc[1][mt][0]; v[2 * mt + 1] = acc[0][mt][2] + acc[1][mt][2]; }
            const int t4 = lane & 3;
            const float a0 = t4 == 0 ? v[0] : t4 == 1 ? v[3] : v[6];
            const float a1 = t4 == 0 ? v[1] : t4 == 1 ? v[4] : v[7];
            const float a2 = t4 == 0 ? v[2] : t4 == 1 ? v[5] : 0.f;
            if (t4 < 3) {
                float o0, o1, o2, cnt;
                float4* ap = &sx->acc[s_tag[1] & 1][(b * 7 + warp) * 32 + lane];
                asm volatile("atom.relaxed.gpu.global.add.v4.f32 {%0,%1,%2,%3}, [%4], {%5,%6,%7,%8};"
                             : "=f"(o0), "=f"(o1), "=f"(o2), "=f"(cnt) : "l"(ap), "f"(a0), "f"(a1), "f"(a2), "f"(1.0f) : "memory");
                if (cnt == 63.f) {
                    if (!pkt_ok(gv, tag)) gv = pkt_poll(g_src, tag);
                    __nv_bfloat16* dst = prm.out + ocol;
                    dst[0] = __float2bfloat16_rn(__bfloat162float(xq[0]) + bf16r(bf16r(o0 + a0) * pkt_f(gv.x)));
                    dst[8] = __float2bfloat16_rn(__bfloat162float(xq[1]) + bf16r(bf16r(o1 + a1) * pkt_f(gv.y)));
                    if (t4 < 2) dst[16] = __float2bfloat16_rn(__bfloat162float(xq[2]) + bf16r(bf16r(o2 + a2) * pkt_f(gv.z)));
                }
            }
        }
        if (false) {
            const bool k = lane & 1;
            pkt_store(s_dst, k ? acc[0][2][0] + acc[1][2][0] : acc[0][0][0] + acc[1][0][0], k ? acc[0][2][2] + acc[1][2][2] : acc[0][0][2] + acc[1][0][2],
                             k ? acc[0][3][0] + acc[1][3][0] : acc[0][1][0] + acc[1][1][0], k ? acc[0][3][2] + acc[1][3][2] : acc[0][1][2] + acc[1][1][2], tag);
        }
        if (tid == 0) STAMP(8);
    }
}

typedef CUresult (*EncodeFn)(CUtensorMap*, CUtensorMapDataType, cuuint32_t, void*, const cuuint64_t*, const cuuint64_t*,
                             const cuuint32_t*, const cuuint32_t*, CUtensorMapInterleave, CUtensorMapSwizzle,
                             CUtensorMapL2promotion, CUtensorMapFloatOOBfill);

void make_map(EncodeFn enc, CUtensorMap* m, const void* ptr, uint64_t cols, uint64_t rows, uint64_t planes,
              uint32_t bc, uint32_t br, uint32_t bp, CUtensorMapSwizzle sw, int promo = 2) {
    cuuint64_t dims[3] = {cols, rows, planes};
    cuuint64_t strides[2] = {cols * 2, cols * rows * 2};
    cuuint32_t box[3] = {bc, br, bp};
    cuuint32_t es[3] = {1, 1, 1};
    enc(m, CU_TENSOR_MAP_DATA_TYPE_BFLOAT16, planes ? 3 : 2, const_cast<void*>(ptr), dims, strides, box, es,
        CU_TENSOR_MAP_INTERLEAVE_NONE, sw, (CUtensorMapL2promotion)promo, CU_TENSOR_MAP_FLOAT_OOB_FILL_NONE);
}

}

extern "C" void kernel_launch(void* const* d_in, const int* in_sizes, int n_in, void* d_out, int out_size) {
    (void)in_sizes; (void)n_in; (void)out_size;
    static EncodeFn enc = nullptr;
    static Scratch* scratch = nullptr;
    if (!enc) {
        void* fn = nullptr;
        cudaDriverEntryPointQueryResult qr;
        cudaGetDriverEntryPoint("cuTensorMapEncodeTiled", &fn, cudaEnableDefault, &qr);
        enc = (EncodeFn)fn;
        cudaGetSymbolAddress((void**)&scratch, g_scratch);
        cudaFuncSetAttribute(fused_decode_kernel, cudaFuncAttributeMaxDynamicSharedMemorySize, SMEM_BYTES);
    }
    Params p;
    p.k = (const uint8_t*)d_in[1];
    p.wq_raw = (const uint8_t*)d_in[3];
    p.wd_raw = (const uint8_t*)d_in[8];
    p.x = (const __nv_bfloat16*)d_in[0];
    p.out = (__nv_bfloat16*)d_out;
    p.sx = scratch;
    make_map(enc, &p.v,  d_in[2], 256,  (uint64_t)16 * SK, 0, 32, 256, 0, CU_TENSOR_MAP_SWIZZLE_64B, VPROMO);
    make_map(enc, &p.wq, d_in[3], 4096, D,    0,  64, 224, 0, CU_TENSOR_MAP_SWIZZLE_128B);
    make_map(enc, &p.wo, d_in[4], D,    256,  16, 64, 32,  2, CU_TENSOR_MAP_SWIZZLE_128B);
    make_map(enc, &p.wg, d_in[6], FF,   D,    0,  64, 224, 0, CU_TENSOR_MAP_SWIZZLE_128B);
    make_map(enc, &p.wu, d_in[7], FF,   D,    0,  64, 224, 0, CU_TENSOR_MAP_SWIZZLE_128B);
    make_map(enc, &p.wd, d_in[8], D,    FF,   0,  64, 128, 0, CU_TENSOR_MAP_SWIZZLE_128B);
    fused_decode_kernel<<<NCTA, NTHREADS, SMEM_BYTES, cudaStreamPerThread>>>(p);
}
```

```cpp
#include <cuda_runtime.h>
#include <cuda_bf16.h>
#include <cuda.h>
#include <stdint.h>

namespace {

constexpr int D = 448, SK = 32768, WIN = 4096, FF = 1792;
constexpr int NMAIN = 128, NHELP = 4, NCTA = NMAIN + NHELP;
constexpr int NS = 9;
constexpr int SLOT = 16384;
constexpr int NT = 16;
constexpr int NTHREADS = 288;

#define KDEPTH 3
#define VDEPTH 2
#define NSTART 2
#define GUPOS 4
#define GUN 4
#define GUT 10
#define WOPOS 22
#define WL 0
#define WLW 0
#define WLN 0
#define TWO 14
#define TG 13
#define TSTAT 6
#define TPRE 3
#define VPROMO 2
#define WDPF 0

__host__ __device__ constexpr int landed(int n) { return n < KDEPTH ? 0 : n < NT ? n - KDEPTH + 1 : n - VDEPTH + 1; }

constexpr int OFF_RING = 0;
constexpr int OFF_W    = OFF_RING + NS * SLOT;
constexpr int OFF_P    = OFF_W + 57344;
constexpr int P_PITCH  = WIN + 8;
constexpr int OFF_XN   = OFF_P + 2 * P_PITCH * 2;
constexpr int XN_PITCH = 456;
constexpr int OFF_Q    = OFF_XN + 2 * XN_PITCH * 2;
constexpr int OFF_ZERO = OFF_Q + 1024;
constexpr int OFF_PART = OFF_ZERO + 16;
constexpr int OFF_PART2 = OFF_PART + 2048;
constexpr int OFF_RED  = OFF_PART2 + 1024;
constexpr int OFF_TAG  = OFF_RED + 128;
constexpr int OFF_BAR  = OFF_TAG + 16;
constexpr int BAR_FULL = OFF_BAR, BAR_EMPTY = BAR_FULL + NS * 8;
constexpr int BAR_WQ = BAR_EMPTY + NS * 8, BAR_GU = BAR_WQ + 8, BAR_WO = BAR_GU + 8, BAR_WFREE = BAR_WO + 7 * 8;
constexpr int SMEM_BYTES = BAR_WFREE + 8 + 1024;
constexpr int H_PITCH = FF + 8;
static_assert(OFF_XN % 16 == 0 && OFF_Q % 16 == 0 && OFF_P % 16 == 0 && OFF_PART % 16 == 0 && OFF_BAR % 8 == 0, "align");
static_assert(SMEM_BYTES <= 232448, "smem");

struct __align__(128) Scratch {
    uint4 sc[16 * 2048];
    uint4 q[NMAIN * 32];
    uint4 h[112 * 32];
    uint4 g[2 * 7 * 32];
    float4 acc[2][2 * 7 * 32];
    unsigned epoch[NCTA];
};
__device__ Scratch g_scratch;

struct Params {
    const uint8_t* wq_raw;
    const uint8_t* k;
    const uint8_t* wd_raw;
    const __nv_bfloat16* x;
    __nv_bfloat16* out;
    Scratch* sx;
    alignas(64) CUtensorMap wq;
    CUtensorMap v, wg, wu, wo, wd;
};

#define CLK(v, dep) do {} while (0)
#define STAMP(i) do {} while (0)

__device__ __forceinline__ uint32_t smem_u32(const void* p) { return (uint32_t)__cvta_generic_to_shared(p); }
__device__ __forceinline__ bool elect_one() {
    uint32_t p;
    asm volatile("{\n.reg .pred P;\nelect.sync _|P, 0xffffffff;\nselp.u32 %0, 1, 0, P;\n}" : "=r"(p));
    return p;
}
__device__ __forceinline__ void mbar_init(uint32_t bar, uint32_t cnt) {
    asm volatile("mbarrier.init.shared::cta.b64 [%0], %1;" :: "r"(bar), "r"(cnt) : "memory");
}
__device__ __forceinline__ void mbar_expect_tx(uint32_t bar, uint32_t bytes) {
    asm volatile("mbarrier.arrive.expect_tx.shared::cta.b64 _, [%0], %1;" :: "r"(bar), "r"(bytes) : "memory");
}
__device__ __forceinline__ void mbar_arrive(uint32_t bar, uint32_t cnt) {
    asm volatile("mbarrier.arrive.shared::cta.b64 _, [%0], %1;" :: "r"(bar), "r"(cnt) : "memory");
}
__device__ __forceinline__ void mbar_wait(uint32_t bar, uint32_t parity) {
    uint32_t ok;
    int it = 0;
    do {
        asm volatile("{\n.reg .pred p;\nmbarrier.test_wait.parity.shared::cta.b64 p, [%1], %2;\nselp.u32 %0, 1, 0, p;\n}"
                     : "=r"(ok) : "r"(bar), "r"(parity) : "memory");
    } while (!ok && ++it < (1 << 24));
}
__device__ __forceinline__ void l2_prefetch(const void* src, uint32_t bytes) {
    asm volatile("cp.async.bulk.prefetch.L2.global [%0], %1;" :: "l"(src), "r"(bytes) : "memory");
}
__device__ __forceinline__ void bulk1d(uint32_t dst, const void* src, uint32_t bytes, uint32_t bar, uint64_t pol) {
    asm volatile("cp.async.bulk.shared::cluster.global.mbarrier::complete_tx::bytes.L2::cache_hint [%0], [%1], %2, [%3], %4;"
                 :: "r"(dst), "l"(src), "r"(bytes), "r"(bar), "l"(pol) : "memory");
}
__device__ __forceinline__ void tma2d(uint32_t dst, const CUtensorMap* map, int c0, int c1, uint32_t bar) {
    asm volatile("cp.async.bulk.tensor.2d.shared::cluster.global.mbarrier::complete_tx::bytes [%0], [%1, {%3, %4}], [%2];"
                 :: "r"(dst), "l"(map), "r"(bar), "r"(c0), "r"(c1) : "memory");
}
__device__ __forceinline__ void tma2d_hint(uint32_t dst, const CUtensorMap* map, int c0, int c1, uint32_t bar, uint64_t pol) {
    asm volatile("cp.async.bulk.tensor.2d.shared::cluster.global.mbarrier::complete_tx::bytes.L2::cache_hint [%0], [%1, {%3, %4}], [%2], %5;"
                 :: "r"(dst), "l"(map), "r"(bar), "r"(c0), "r"(c1), "l"(pol) : "memory");
}
__device__ __forceinline__ void tma5d(uint32_t dst, const CUtensorMap* map, int c0, int c1, int c4, uint32_t bar) {
    asm volatile("cp.async.bulk.tensor.5d.shared::cluster.global.mbarrier::complete_tx::bytes [%0], [%1, {%3, %4, %6, %6, %5}], [%2];"
                 :: "r"(dst), "l"(map), "r"(bar), "r"(c0), "r"(c1), "r"(c4), "r"(0) : "memory");
}
__device__ __forceinline__ void ldsm4(uint32_t (&r)[4], uint32_t addr) {
    asm volatile("ldmatrix.sync.aligned.m8n8.x4.shared.b16 {%0,%1,%2,%3}, [%4];"
                 : "=r"(r[0]), "=r"(r[1]), "=r"(r[2]), "=r"(r[3]) : "r"(addr) : "memory");
}
__device__ __forceinline__ void ldsm4t(uint32_t (&r)[4], uint32_t addr) {
    asm volatile("ldmatrix.sync.aligned.m8n8.x4.trans.shared.b16 {%0,%1,%2,%3}, [%4];"
                 : "=r"(r[0]), "=r"(r[1]), "=r"(r[2]), "=r"(r[3]) : "r"(addr) : "memory");
}
__device__ __forceinline__ void lds128(uint32_t (&r)[4], uint32_t addr) {
    asm volatile("ld.shared.v4.u32 {%0,%1,%2,%3}, [%4];"
                 : "=r"(r[0]), "=r"(r[1]), "=r"(r[2]), "=r"(r[3]) : "r"(addr) : "memory");
}
__device__ __forceinline__ void mma16816(float (&c)[4], uint32_t a0, uint32_t a1, uint32_t a2, uint32_t a3, uint32_t b0, uint32_t b1) {
    asm volatile("mma.sync.aligned.m16n8k16.row.col.f32.bf16.bf16.f32 {%0,%1,%2,%3}, {%4,%5,%6,%7}, {%8,%9}, {%0,%1,%2,%3};"
                 : "+f"(c[0]), "+f"(c[1]), "+f"(c[2]), "+f"(c[3])
                 : "r"(a0), "r"(a1), "r"(a2), "r"(a3), "r"(b0), "r"(b1));
}
__device__ __forceinline__ void mma16816(float (&c)[4], const uint32_t (&a)[4], uint32_t b0, uint32_t b1) {
    mma16816(c, a[0], a[1], a[2], a[3], b0, b1);
}
__device__ __forceinline__ void bar_sync(int id, int n) { asm volatile("bar.sync %0, %1;" :: "r"(id), "r"(n) : "memory"); }
__device__ __forceinline__ void bar_arrive(int id, int n) { asm volatile("bar.arrive %0, %1;" :: "r"(id), "r"(n) : "memory"); }
__device__ __forceinline__ uint32_t pack_bf16(float lo, float hi) {
    uint32_t r;
    asm("cvt.rn.bf16x2.f32 %0, %1, %2;" : "=r"(r) : "f"(hi), "f"(lo));
    return r;
}
__device__ __forceinline__ float bf16r(float v) { return __uint_as_float(pack_bf16(0.f, v)); }

__device__ __forceinline__ __nv_bfloat16 geglu(float gate, float up) {
    const float ga = bf16r(gate);
    const float in = 0.7978845608028654f * (ga + 0.044715f * ga * ga * ga);
    return __float2bfloat16_rn(bf16r(0.5f * ga * (1.0f + tanhf(in))) * bf16r(up));
}

__device__ __forceinline__ void ldB(uint32_t (&r)[4], uint32_t base, int pitch_bytes, int k0, uint32_t zero, int lane) {
    const int n = lane & 7;
    ldsm4(r, n < 2 ? base + n * pitch_bytes + (k0 + 8 * (lane >> 3)) * 2 : zero);
}

__device__ __forceinline__ void pkt_store(uint4* p, float a, float b, float c, float d, uint32_t tag) {
    const uint32_t w0 = (__float_as_uint(a) & ~3u) | (tag & 3u);
    const uint32_t w1 = (__float_as_uint(b) & ~3u) | ((tag >> 2) & 3u);
    const uint32_t w2 = (__float_as_uint(c) & ~3u) | ((tag >> 4) & 3u);
    const uint32_t w3 = (__float_as_uint(d) & ~3u) | ((tag >> 6) & 3u);
    asm volatile("{\n.reg .b128 t;\n.reg .b64 lo, hi;\nmov.b64 lo, {%1, %2};\nmov.b64 hi, {%3, %4};\nmov.b128 t, {lo, hi};\n"
                 "st.relaxed.gpu.global.b128 [%0], t;\n}"
                 :: "l"(p), "r"(w0), "r"(w1), "r"(w2), "r"(w3) : "memory");
}
__device__ __forceinline__ void pkt_clear(uint4* p) { pkt_store(p, 0.f, 0.f, 0.f, 0.f, 0); }
__device__ __forceinline__ uint4 pkt_load(const uint4* p) {
    uint4 v;
    asm volatile("{\n.reg .b128 t;\n.reg .b64 lo, hi;\nld.relaxed.gpu.global.b128 t, [%4];\nmov.b128 {lo, hi}, t;\n"
                 "mov.b64 {%0, %1}, lo;\nmov.b64 {%2, %3}, hi;\n}"
                 : "=r"(v.x), "=r"(v.y), "=r"(v.z), "=r"(v.w) : "l"(p) : "memory");
    return v;
}
__device__ __forceinline__ uint32_t pkt_diff(const uint4& v, uint32_t tag) {
    return ((v.x ^ tag) | (v.y ^ (tag >> 2))) | ((v.z ^ (tag >> 4)) | (v.w ^ (tag >> 6)));
}
__device__ __forceinline__ float pkt_f(uint32_t w) { return __uint_as_float(w & ~3u); }
constexpr int POLL_MAX = 1 << 20;

__global__ void __launch_bounds__(NTHREADS, 1) fused_decode_kernel(const __grid_constant__ Params prm) {
    extern __shared__ uint8_t smem_raw[];
    const int cta = blockIdx.x;
    const int tid = threadIdx.x, lane = tid & 31;
    const bool is_main = cta < NMAIN;
    if (tid == 0 && is_main) l2_prefetch(prm.wq_raw + cta * 28672, 28672);
    const int warp = __shfl_sync(~0u, tid >> 5, 0);

    const uint32_t sb = (smem_u32(smem_raw) + 1023u) & ~1023u;
    const int grp = cta >> 3, j = cta & 7;
    const int b = grp >> 3;
    const bool has_ffn = is_main && j < 7;
    const int fblk = grp * 7 + j;
    const int qblk = (grp & 7) * 16 + b * 8 + j;
    const int ncg = is_main ? 0 : (cta - NMAIN < 3 ? 2 : 1);
    const int cg0 = (cta - NMAIN) * 2;
    Scratch* const sx = prm.sx;
    uint8_t* const sm = smem_raw + (sb - smem_u32(smem_raw));
    volatile uint32_t* const s_tag = reinterpret_cast<volatile uint32_t*>(sm + OFF_TAG);

    if (warp == 8) {
        const bool leader = elect_one();
        const uint8_t* const ksrc = prm.k + ((size_t)grp * SK + (SK - WIN) + j * 32) * 512;
        uint64_t pol;
        asm volatile("createpolicy.fractional.L2::evict_first.b64 %0, 1.0;" : "=l"(pol));
        if (leader) {
#pragma unroll
            for (int i = 0; i < NSTART; i++) mbar_init(sb + BAR_FULL + i * 8, 1);
            mbar_init(sb + BAR_WQ, 1);
            asm volatile("fence.mbarrier_init.release.cluster;" ::: "memory");
            if (is_main) {
                mbar_expect_tx(sb + BAR_WQ, 28672);
                tma2d(sb + OFF_W, &prm.wq, (qblk >> 1) * 64, (qblk & 1) * 224, sb + BAR_WQ);
#pragma unroll
                for (int i = 0; i < NSTART; i++) {
                    mbar_expect_tx(sb + BAR_FULL + i * 8, SLOT);
                    bulk1d(sb + OFF_RING + i * SLOT, ksrc + (size_t)i * 256 * 512, SLOT, sb + BAR_FULL + i * 8, pol);
                }
            }
#pragma unroll
            for (int i = NSTART; i < NS; i++) mbar_init(sb + BAR_FULL + i * 8, 1);
#pragma unroll
            for (int i = 0; i < NS; i++) mbar_init(sb + BAR_EMPTY + i * 8, 8);
            mbar_init(sb + BAR_GU, 1); mbar_init(sb + BAR_WFREE, 8);
#pragma unroll
            for (int c = 0; c < 7; c++) mbar_init(sb + BAR_WO + c * 8, 1);
            asm volatile("fence.mbarrier_init.release.cluster;" ::: "memory");
        }
        __syncthreads();
        if (is_main) {
            if (leader) {
                asm volatile("prefetch.tensormap [%0];" :: "l"((fblk & 1) ? &prm.wu : &prm.wg) : "memory");
                asm volatile("prefetch.tensormap [%0];" :: "l"(&prm.v) : "memory");
                asm volatile("prefetch.tensormap [%0];" :: "l"(&prm.wo) : "memory");
            }
            const int vrow = grp * SK + (SK - WIN);
#pragma unroll
            for (int n = NSTART; n < 2 * NT; n++) {
                const uint32_t bar = sb + BAR_FULL + (n % NS) * 8, dst = sb + OFF_RING + (n % NS) * SLOT;
                if (n >= NS) mbar_wait(sb + BAR_EMPTY + (n % NS) * 8, (n / NS - 1) & 1);
                if (n == WOPOS) mbar_wait(sb + BAR_WFREE, 0);
                if (leader) {
                    mbar_expect_tx(bar, SLOT);
                    if (n == GUPOS && has_ffn) mbar_expect_tx(sb + BAR_GU, 28672);
                    if (n == WOPOS) {
#pragma unroll
                        for (int c = 0; c < 7; c++) mbar_expect_tx(sb + BAR_WO + c * 8, 8192);
                    }
                }
                if (n == NSTART) mbar_wait(sb + BAR_WQ, 0);
#pragma unroll
                for (int w = landed(n - 1); w < landed(n); w++) mbar_wait(sb + BAR_FULL + (w % NS) * 8, (w / NS) & 1);
                if (leader) {
                    if (n < NT) bulk1d(dst, ksrc + (size_t)n * 256 * 512, SLOT, bar, pol);
                    else        tma2d_hint(dst, &prm.v, j * 32, vrow + (n - NT) * 256, bar, pol);
                    if (n >= GUPOS && n < GUPOS + GUN && has_ffn)
                        tma2d(sb + OFF_W + 28672 + (n - GUPOS) * (28672 / GUN), (fblk & 1) ? &prm.wu : &prm.wg, (fblk >> 2) * 64,
                              ((fblk >> 1) & 1) * 224 + (n - GUPOS) * (224 / GUN), sb + BAR_GU);
                    if (n >= WOPOS && n < WOPOS + 7 - WL)
                        tma5d(sb + OFF_W + (n - WOPOS) * 8192, &prm.wo, (n - WOPOS) * 64, (grp & 7) * 2, j * 2, sb + BAR_WO + (n - WOPOS) * 8);
                }
            }
#pragma unroll
            for (int c = 7 - WL; c < 7; c++) {
                if (c == 7 - WL && WLW) mbar_wait(sb + BAR_FULL + (WLW % NS) * 8, (WLW / NS) & 1);
                if (c == 7 - WL + WLN && WLN) mbar_wait(sb + BAR_FULL + ((WLW + 1) % NS) * 8, ((WLW + 1) / NS) & 1);
                if (leader) tma5d(sb + OFF_W + c * 8192, &prm.wo, c * 64, (grp & 7) * 2, j * 2, sb + BAR_WO + c * 8);
            }
            if (cta < 14) sx->acc[(s_tag[1] + 1) & 1][cta * 32 + lane] = make_float4(0.f, 0.f, 0.f, 0.f);
        } else {
            int slot = 0, ph = 1;
            for (int n = 0; n < 14 * ncg; n++) {
                if (n >= NS) mbar_wait(sb + BAR_EMPTY + slot * 8, ph);
                if (leader) {
                    mbar_expect_tx(sb + BAR_FULL + slot * 8, SLOT);
                    tma2d(sb + OFF_RING + slot * SLOT, &prm.wd, (cg0 + (ncg == 2 ? (n & 1) : 0)) * 64, (ncg == 2 ? (n >> 1) : n) * 128,
                          sb + BAR_FULL + slot * 8);
                }
                if (WDPF && n >= 1 && n < NS) {
                    if (n >= 2) mbar_wait(sb + BAR_FULL + (n - 2) * 8, 0);
                    if (leader) l2_prefetch(prm.wd_raw + (size_t)(512 + (cta - NMAIN) * 320 + (n - 1) * 40) * 896, 40 * 896);
                }
                if (++slot == NS) { slot = 0; ph ^= 1; }
            }
        }
        return;
    }

    const uint32_t zero = sb + OFF_ZERO;
    float* const s_part = reinterpret_cast<float*>(sm + OFF_PART);
    float* const s_red = reinterpret_cast<float*>(sm + OFF_RED);
    uint32_t xw[7];
    if (warp < 2 && is_main) {
        const uint32_t* xp = reinterpret_cast<const uint32_t*>(prm.x + warp * D);
#pragma unroll
        for (int i = 0; i < 7; i++) xw[i] = __ldg(xp + lane + 32 * i);
    }
    unsigned epoch = 0;
    if (tid == 64) epoch = sx->epoch[cta];
    if (tid == 96) *reinterpret_cast<uint4*>(sm + OFF_ZERO) = make_uint4(0, 0, 0, 0);
    if (is_main) {
        if (warp == 4) pkt_clear(&sx->q[qblk * 32 + lane]);
        if (warp == 5 && has_ffn) pkt_clear(&sx->h[fblk * 32 + lane]);
    } else if (warp < ncg * 2) {
        pkt_clear(&sx->g[((warp & 1) * 7 + cg0 + (warp >> 1)) * 32 + lane]);
    }
    __syncthreads();

    if (!is_main) {
        if (tid == 64) { sx->epoch[cta] = epoch + 1; s_tag[0] = epoch % 255u + 1u; }
        bar_sync(1, 256);
        const uint32_t tag = s_tag[0];
        __nv_bfloat16* h_s = reinterpret_cast<__nv_bfloat16*>(sm + OFF_W);
        {
            uint4 v[4][4];
            const int ncb = warp < 4 ? 4 : 3;
            int it = 0;
            uint32_t bad;
            do {
                if (it) __nanosleep(400);
                bad = 0;
#pragma unroll
                for (int i = 0; i < 4; i++)
#pragma unroll
                    for (int q = 0; q < 4; q++)
                        if (i < ncb) v[i][q] = pkt_load(&sx->h[(warp + 8 * i) * 128 + q * 32 + lane]);
#pragma unroll
                for (int i = 0; i < 4; i++)
                    if (i < ncb) bad |= (pkt_diff(v[i][0], tag) | pkt_diff(v[i][1], tag)) | (pkt_diff(v[i][2], tag) | pkt_diff(v[i][3], tag));
            } while ((bad & 3u) && ++it < POLL_MAX);
#pragma unroll
            for (int i = 0; i < 4; i++) {
                if (i < ncb) {
                    __nv_bfloat16* dst = h_s + (warp + 8 * i) * 64 + (lane >> 3) * 16 + (lane & 7);
                    dst[0]           = geglu(pkt_f(v[i][0].x) + pkt_f(v[i][2].x), pkt_f(v[i][1].x) + pkt_f(v[i][3].x));
                    dst[H_PITCH]     = geglu(pkt_f(v[i][0].y) + pkt_f(v[i][2].y), pkt_f(v[i][1].y) + pkt_f(v[i][3].y));
                    dst[8]           = geglu(pkt_f(v[i][0].z) + pkt_f(v[i][2].z), pkt_f(v[i][1].z) + pkt_f(v[i][3].z));
                    dst[H_PITCH + 8] = geglu(pkt_f(v[i][0].w) + pkt_f(v[i][2].w), pkt_f(v[i][1].w) + pkt_f(v[i][3].w));
                }
            }
        }
        bar_sync(1, 256);
        if (tid == 0) STAMP(10);
        const int mt = warp & 3, kh = warp >> 2;
        float acc[2][4] = {};
        int slot = 0, ph = 0;
        for (int rb = 0; rb < 14; rb++) {
            uint32_t bf[2][4];
            ldB(bf[0], sb + OFF_W, H_PITCH * 2, rb * 128 + kh * 64, zero, lane);
            ldB(bf[1], sb + OFF_W, H_PITCH * 2, rb * 128 + kh * 64 + 32, zero, lane);
#pragma unroll
            for (int ci = 0; ci < 2; ci++) {
                if (ci < ncg) {
                    mbar_wait(sb + BAR_FULL + slot * 8, ph);
                    const uint32_t base = sb + OFF_RING + slot * SLOT;
#pragma unroll
                    for (int ks = 0; ks < 4; ks++) {
                        const int row = kh * 64 + ks * 16 + (lane & 7) + 8 * (lane >> 4);
                        const int ch = 2 * mt + ((lane >> 3) & 1);
                        uint32_t a[4];
                        ldsm4t(a, base + row * 128 + ((ch ^ (row & 7)) << 4));
                        mma16816(acc[ci], a, bf[ks >> 1][(ks & 1) * 2], bf[ks >> 1][(ks & 1) * 2 + 1]);
                    }
                    __syncwarp();
                    if (lane == 0) mbar_arrive(sb + BAR_EMPTY + slot * 8, 1);
                    if (++slot == NS) { slot = 0; ph ^= 1; }
                }
            }
        }
        if ((lane & 3) == 0) {
#pragma unroll
            for (int ci = 0; ci < 2; ci++) {
                float* p = s_part + kh * 256 + ci * 128 + (mt * 16 + (lane >> 2)) * 2;
                p[0] = acc[ci][0]; p[1] = acc[ci][1]; p[16] = acc[ci][2]; p[17] = acc[ci][3];
            }
        }
        bar_sync(1, 256);
        if (warp < ncg * 2) {
            const int ci = warp >> 1, bb = warp & 1;
            float g[3];
#pragma unroll
            for (int i = 0; i < 3; i++) {
                const int col = ((lane >> 2) + 8 * (3 * (lane & 3) + i)) & 63;
                const float y = bf16r(s_part[ci * 128 + col * 2 + bb] + s_part[256 + ci * 128 + col * 2 + bb]);
                g[i] = bf16r(y / (1.0f + expf(-y)));
            }
            pkt_store(&sx->g[(bb * 7 + cg0 + ci) * 32 + lane], g[0], g[1], g[2], 0.f, tag);
        }
        if (tid == 0) STAMP(11);
        return;
    }

    if (warp < 2) {
        float xv[14], sum = 0.f;
#pragma unroll
        for (int i = 0; i < 7; i++) {
            xv[2 * i] = __uint_as_float(xw[i] << 16);
            xv[2 * i + 1] = __uint_as_float(xw[i] & 0xffff0000u);
            sum += xv[2 * i] + xv[2 * i + 1];
        }
#pragma unroll
        for (int o = 16; o; o >>= 1) sum += __shfl_xor_sync(~0u, sum, o);
        const float mean = sum * (1.0f / D);
        float var = 0.f;
#pragma unroll
        for (int i = 0; i < 14; i++) { const float d = xv[i] - mean; var += d * d; }
#pragma unroll
        for (int o = 16; o; o >>= 1) var += __shfl_xor_sync(~0u, var, o);
        const float mb = bf16r(mean);
        const float sd = bf16r(sqrtf(bf16r(bf16r(var * (1.0f / D)) + 1e-5f)));
        uint32_t* xn = reinterpret_cast<uint32_t*>(sm + OFF_XN + warp * XN_PITCH * 2);
#pragma unroll
        for (int i = 0; i < 7; i++) xn[lane + 32 * i] = pack_bf16(bf16r(xv[2 * i] - mb) / sd, bf16r(xv[2 * i + 1] - mb) / sd);
    }
    if (tid == 64) { sx->epoch[cta] = epoch + 1; s_tag[0] = epoch % 255u + 1u; s_tag[1] = epoch; }
    bar_sync(1, 256);
    const uint32_t tag = s_tag[0];
    float4* const acc_dst = &sx->acc[s_tag[1] & 1][(b * 7 + warp) * 32 + lane];

    auto project = [&](uint32_t wbase, int khalf, uint32_t bar, uint4* dst) {
        uint32_t xb[7][4];
#pragma unroll
        for (int i = 0; i < 7; i++) ldB(xb[i], sb + OFF_XN, XN_PITCH * 2, khalf * 224 + i * 32, zero, lane);
        float acc[2][4] = {};
        mbar_wait(bar, 0);
#pragma unroll
        for (int ks = 0; ks < 14; ks++) {
            const int row = ks * 16 + (lane & 7) + 8 * (lane >> 4);
            const int ch = 2 * (warp & 3) + ((lane >> 3) & 1);
            uint32_t a[4];
            ldsm4t(a, wbase + row * 128 + ((ch ^ (row & 7)) << 4));
            mma16816(acc[ks & 1], a, xb[ks >> 1][(ks & 1) * 2], xb[ks >> 1][(ks & 1) * 2 + 1]);
        }
        if ((lane & 3) == 0)
            pkt_store(dst + (warp & 3) * 8 + (lane >> 2), acc[0][0] + acc[1][0], acc[0][1] + acc[1][1], acc[0][2] + acc[1][2], acc[0][3] + acc[1][3], tag);
        __syncwarp();
        if (lane == 0) mbar_arrive(sb + BAR_WFREE, 1);
    };
    if (warp < 4) {
        project(sb + OFF_W, qblk & 1, sb + BAR_WQ, &sx->q[qblk * 32]);
    } else {
        if (!has_ffn && lane == 0) mbar_arrive(sb + BAR_WFREE, 1);
        mbar_wait(sb + BAR_WQ, 0);
    }
    if (tid == 0) STAMP(2);
    {
        const uint4* src = &sx->q[((grp & 7) * 8 + warp) * 64 + lane];
        uint4 u, v;
        int it = 0;
        do { u = pkt_load(src); v = pkt_load(src + 32); } while (((pkt_diff(u, tag) | pkt_diff(v, tag)) & 3u) && ++it < POLL_MAX);
        __nv_bfloat16* dst = reinterpret_cast<__nv_bfloat16*>(sm + OFF_Q) + warp * 64 + (lane >> 3) * 16 + (lane & 7);
        dst[0] = __float2bfloat16_rn(pkt_f(b ? u.y : u.x) + pkt_f(b ? v.y : v.x));
        dst[8] = __float2bfloat16_rn(pkt_f(b ? u.w : u.z) + pkt_f(b ? v.w : v.z));
    }
    bar_sync(1, 256);
    if (tid == 0) STAMP(3);

    const int pidx = ((lane >> 4) * 8 + warp) * 16 + (lane & 15);
    const uint4* const sc_src = &sx->sc[grp * 2048 + pidx];
    uint4 sv[4];
    {
        const int g = lane >> 2, t4 = lane & 3;
        uint32_t qb[8][4];
#pragma unroll
        for (int i = 0; i < 8; i++) lds128(qb[i], sb + OFF_Q + (g & 1) * 512 + ((i ^ ((g >> 1) & 1)) * 32 + t4 * 8) * 2);
        const int mt = warp & 1;
        const uint32_t roff = (mt * 16 + 2 * g) * 512 + t4 * 16;
        for (int t = 0; t < NT; t++) {
            const int slot = t % NS;
            if ((slot & 3) != (warp >> 1)) continue;
            if (t >= GUT && t < GUT + 4 && warp >= 4 && has_ffn) project(sb + OFF_W + 28672, (fblk >> 1) & 1, sb + BAR_GU, &sx->h[fblk * 32]);
            if (t >= NT - 4) {
#pragma unroll
                for (int i = 0; i < 4; i++) sv[i] = pkt_load(sc_src + i * 256);
            }
            mbar_wait(sb + BAR_FULL + slot * 8, (t / NS) & 1);
            const uint32_t base = sb + OFF_RING + slot * SLOT + roff;
            float acc0[4] = {}, acc1[4] = {};
#pragma unroll
            for (int i = 0; i < 8; i++) {
                uint32_t r0[4], r1[4];
                const uint32_t a = base + ((i ^ (g & 1)) << 6);
                lds128(r0, a);
                lds128(r1, a + 512);
                mma16816(acc0, r0[0], r1[0], r0[1], r1[1], qb[i][0], qb[i][1]);
                mma16816(acc1, r0[2], r1[2], r0[3], r1[3], qb[i][2], qb[i][3]);
            }
            __syncwarp();
            if (lane == 0) mbar_arrive(sb + BAR_EMPTY + slot * 8, 4);
            if (t4 == (g & 1)) {
                pkt_store(&sx->sc[grp * 2048 + ((t * 8 + j) * 2 + mt) * 8 + g],
                          bf16r(acc0[0] + acc1[0]) * 0.0625f, bf16r(acc0[2] + acc1[2]) * 0.0625f,
                          bf16r(acc0[1] + acc1[1]) * 0.0625f, bf16r(acc0[3] + acc1[3]) * 0.0625f, tag);
            }
        }
    }
    if (tid == 0) STAMP(4);

    static_assert(landed(12) > NT - NS && VDEPTH <= KDEPTH && NS >= NT / 2 + 1 && TSTAT < NT / 2 + 1, "pipeline shape");
    const int ocol = b * D + warp * 64 + (lane >> 2) + 24 * ((lane & 3) < 3 ? (lane & 3) : 0);
    const uint4* const g_src = &sx->g[(b * 7 + warp) * 32 + lane];
    __nv_bfloat16* const out_dst = prm.out + ocol;
    uint4 gv;
    uint32_t ckw = 0, ck0 = 0, ck1 = 0, ck2 = 0, ck3 = 0, ckb = 0;
    float xq[3];
    float oacc[2][4] = {};
    uint32_t wa[4][4][4];
    const int chb = (lane >> 3) & 1;
    {
        const float L2E = 1.4426950408889634f;
        uint32_t* const p0 = reinterpret_cast<uint32_t*>(sm + OFF_P) + pidx;
        uint32_t* const p1 = reinterpret_cast<uint32_t*>(sm + OFF_P + P_PITCH * 2) + pidx;
        float m0 = -INFINITY, m1 = -INFINITY, l0 = 0.f, l1 = 0.f, f0 = 1.f, f1 = 1.f;
        int slot = NT % NS, ph = (NT / NS) & 1;
        const int rowl = warp * 32 + (lane & 7) + 8 * (lane >> 4);
        const uint32_t voff = rowl * 64, vch0 = (chb ^ ((rowl >> 1) & 3)) << 4, vch1 = ((2 + chb) ^ ((rowl >> 1) & 3)) << 4;
#pragma unroll 1
        for (int t = 0; t < NT / 2; t++) {
            if (t == TSTAT - TPRE) {
#pragma unroll
                for (int i = 0; i < 4; i++) sv[i] = pkt_load(sc_src + (4 + i) * 256);
            }
            if (t == 0 || t == TSTAT) {
                const int i0 = t ? 4 : 0;
                int it = 0;
                while ((((pkt_diff(sv[0], tag) | pkt_diff(sv[1], tag)) | (pkt_diff(sv[2], tag) | pkt_diff(sv[3], tag))) & 3u) && ++it < POLL_MAX) {
#pragma unroll
                    for (int i = 0; i < 4; i++) sv[i] = pkt_load(sc_src + (i0 + i) * 256);
                }
                float e[4][4];
                float n0 = m0, n1 = m1;
#pragma unroll
                for (int i = 0; i < 4; i++) {
                    e[i][0] = pkt_f(sv[i].x); e[i][1] = pkt_f(sv[i].y); e[i][2] = pkt_f(sv[i].z); e[i][3] = pkt_f(sv[i].w);
                    n0 = fmaxf(n0, fmaxf(e[i][0], e[i][1])); n1 = fmaxf(n1, fmaxf(e[i][2], e[i][3]));
                }
#pragma unroll
                for (int o = 16; o; o >>= 1) {
                    n0 = fmaxf(n0, __shfl_xor_sync(~0u, n0, o));
                    n1 = fmaxf(n1, __shfl_xor_sync(~0u, n1, o));
                }
                l0 *= exp2f((m0 - n0) * L2E); l1 *= exp2f((m1 - n1) * L2E);
#pragma unroll
                for (int i = 0; i < 4; i++) {
                    e[i][0] = exp2f((e[i][0] - n0) * L2E); e[i][1] = exp2f((e[i][1] - n0) * L2E);
                    e[i][2] = exp2f((e[i][2] - n1) * L2E); e[i][3] = exp2f((e[i][3] - n1) * L2E);
                    l0 += e[i][0] + e[i][1]; l1 += e[i][2] + e[i][3];
                }
                float c0 = 1.f, c1 = 1.f;
                if (t) {
#pragma unroll
                    for (int o = 16; o; o >>= 1) {
                        l0 += __shfl_xor_sync(~0u, l0, o);
                        l1 += __shfl_xor_sync(~0u, l1, o);
                    }
                    if (lane == 0) *reinterpret_cast<float4*>(s_red + warp * 4) = make_float4(n0, l0, n1, l1);
                    bar_sync(1, 256);
                    const float4 st = *reinterpret_cast<const float4*>(s_red + (lane & 7) * 4);
                    float M0 = st.x, M1 = st.z;
#pragma unroll
                    for (int o = 4; o; o >>= 1) {
                        M0 = fmaxf(M0, __shfl_xor_sync(~0u, M0, o));
                        M1 = fmaxf(M1, __shfl_xor_sync(~0u, M1, o));
                    }
                    float L0 = st.y * exp2f((st.x - M0) * L2E), L1 = st.w * exp2f((st.z - M1) * L2E);
#pragma unroll
                    for (int o = 4; o; o >>= 1) {
                        L0 += __shfl_xor_sync(~0u, L0, o);
                        L1 += __shfl_xor_sync(~0u, L1, o);
                    }
                    c0 = exp2f((n0 - M0) * L2E) / L0; c1 = exp2f((n1 - M1) * L2E) / L1;
                    f0 = exp2f((m0 - M0) * L2E) / L0; f1 = exp2f((m1 - M1) * L2E) / L1;
                }
                m0 = n0; m1 = n1;
#pragma unroll
                for (int i = 0; i < 4; i++) {
                    p0[(i0 + i) * 256] = pack_bf16(e[i][0] * c0, e[i][1] * c0);
                    p1[(i0 + i) * 256] = pack_bf16(e[i][2] * c1, e[i][3] * c1);
                }
                __syncwarp();
                if (tid == 0) STAMP(t ? 15 : 14);
            }
            uint32_t pb[4];
            ldB(pb, sb + OFF_P, P_PITCH * 2, t * 256 + warp * 32, zero, lane);
            mbar_wait(sb + BAR_FULL + slot * 8, ph);
            const uint32_t base = sb + OFF_RING + slot * SLOT + voff;
#pragma unroll
            for (int ks = 0; ks < 2; ks++) {
                uint32_t a0[4], a1[4];
                ldsm4t(a0, base + ks * 1024 + vch0);
                ldsm4t(a1, base + ks * 1024 + vch1);
                mma16816(oacc[0], a0, pb[ks * 2], pb[ks * 2 + 1]);
                mma16816(oacc[1], a1, pb[ks * 2], pb[ks * 2 + 1]);
            }
            __syncwarp();
            if (lane == 0) mbar_arrive(sb + BAR_EMPTY + slot * 8, 1);
            if (++slot == NS) { slot = 0; ph ^= 1; }
        }
        if ((lane & 3) == 0) {
#pragma unroll
            for (int mt = 0; mt < 2; mt++)
                *reinterpret_cast<float4*>(s_part + warp * 64 + mt * 32 + lane) =
                    make_float4(oacc[mt][0] * f0, oacc[mt][1] * f1, oacc[mt][2] * f0, oacc[mt][3] * f1);
        }
        bar_sync(1, 256);
        float o0[4] = {}, o1[4] = {}, o2[4] = {}, o3[4] = {};
        if ((lane & 3) == 0) {
            const float4 u = *reinterpret_cast<const float4*>(s_part + (warp & 6) * 64 + (warp & 1) * 32 + lane);
            const float4 v = *reinterpret_cast<const float4*>(s_part + (warp | 1) * 64 + (warp & 1) * 32 + lane);
            o0[0] = u.x; o0[1] = u.y; o0[2] = u.z; o0[3] = u.w;
            o1[0] = v.x; o1[1] = v.y; o1[2] = v.z; o1[3] = v.w;
        }
        const int row2 = (warp >> 1) * 64 + (lane & 7) + 8 * (lane >> 4);
        const uint32_t voff2 = row2 * 64 + (((2 * (warp & 1) + chb) ^ ((row2 >> 1) & 3)) << 4);
#pragma unroll
        for (int t = NT / 2; t < NT; t++) {
            if (t == TG && warp < 7) {
                gv = pkt_load(g_src);
                const __nv_bfloat16* xp = prm.x + ocol;
                xq[0] = __bfloat162float(xp[0]); xq[1] = __bfloat162float(xp[8]); xq[2] = __bfloat162float(xp[(lane & 3) < 2 ? 16 : 0]);
            }
            if (t == TWO && warp < 7 - WL) {
                mbar_wait(sb + BAR_WO + warp * 8, 0);
#pragma unroll
                for (int mt = 0; mt < 4; mt++)
#pragma unroll
                    for (int ks = 0; ks < 4; ks++) {
                        const int row = ks * 16 + (lane & 7) + 8 * (lane >> 4);
                        ldsm4t(wa[mt][ks], sb + OFF_W + warp * 8192 + row * 128 + (((2 * mt + chb) ^ (row & 7)) << 4));
                    }
            }
            uint32_t pb[2][4];
            ldB(pb[0], sb + OFF_P, P_PITCH * 2, t * 256 + (warp >> 1) * 64, zero, lane);
            ldB(pb[1], sb + OFF_P, P_PITCH * 2, t * 256 + (warp >> 1) * 64 + 32, zero, lane);
            mbar_wait(sb + BAR_FULL + ((NT + t) % NS) * 8, ((NT + t) / NS) & 1);
            if (t == NT - 1) CLK(ckw, t);
            const uint32_t base = sb + OFF_RING + ((NT + t) % NS) * SLOT + voff2;
            uint32_t a[4][4];
            ldsm4t(a[0], base); ldsm4t(a[1], base + 1024); ldsm4t(a[2], base + 2048); ldsm4t(a[3], base + 3072);
            mma16816(o0, a[0], pb[0][0], pb[0][1]);
            mma16816(o1, a[1], pb[0][2], pb[0][3]);
            mma16816(o2, a[2], pb[1][0], pb[1][1]);
            mma16816(o3, a[3], pb[1][2], pb[1][3]);
        }
        CLK(ck0, __float_as_uint(o0[0] + o1[0]));
        if (tid == 0) STAMP(5);
        if ((lane & 3) == 0)
            *reinterpret_cast<float4*>(sm + OFF_PART2 + ((warp >> 1) * 64 + (warp & 1) * 32 + lane) * 4) =
                make_float4((o0[0] + o1[0]) + (o2[0] + o3[0]), (o0[1] + o1[1]) + (o2[1] + o3[1]),
                            (o0[2] + o1[2]) + (o2[2] + o3[2]), (o0[3] + o1[3]) + (o2[3] + o3[3]));
    }
    if (warp == 7) { bar_arrive(2, 256); return; }
    bar_sync(2, 256);
    if (tid == 0) STAMP(7);
    const float2* pp = reinterpret_cast<const float2*>(sm + OFF_PART2) + lane;
    const float2 v0 = pp[0], v1 = pp[32], v2 = pp[64], v3 = pp[96];
    CLK(ckb, __float_as_uint(v0.x));
    const uint32_t ow = pack_bf16((v0.x + v1.x) + (v2.x + v3.x), (v0.y + v1.y) + (v2.y + v3.y));
    CLK(ck1, ow);
    if (WL && warp >= 7 - WL) {
        mbar_wait(sb + BAR_WO + warp * 8, 0);
#pragma unroll
        for (int ks = 0; ks < 4; ks++)
#pragma unroll
            for (int mt = 0; mt < 4; mt++) {
                const int row = ks * 16 + (lane & 7) + 8 * (lane >> 4);
                ldsm4t(wa[mt][ks], sb + OFF_W + warp * 8192 + row * 128 + (((2 * mt + chb) ^ (row & 7)) << 4));
            }
    }
    float acc[2][4][4] = {};
#pragma unroll
    for (int ks = 0; ks < 4; ks++) {
        const uint32_t b0 = __shfl_sync(~0u, ow, ks * 8 + (lane & 3));
        const uint32_t b1 = __shfl_sync(~0u, ow, ks * 8 + 4 + (lane & 3));
#pragma unroll
        for (int mt = 0; mt < 4; mt++) mma16816(acc[ks & 1][mt], wa[mt][ks], b0, b1);
    }
    const int t4 = lane & 3;
    const float a0 = t4 == 0 ? acc[0][0][0] + acc[1][0][0] : t4 == 1 ? acc[0][1][2] + acc[1][1][2] : acc[0][3][0] + acc[1][3][0];
    const float a1 = t4 == 0 ? acc[0][0][2] + acc[1][0][2] : t4 == 1 ? acc[0][2][0] + acc[1][2][0] : acc[0][3][2] + acc[1][3][2];
    const float a2 = t4 == 0 ? acc[0][1][0] + acc[1][1][0] : t4 == 1 ? acc[0][2][2] + acc[1][2][2] : 0.f;
    CLK(ck2, __float_as_uint(a0));
    if (t4 < 3) {
        float o0, o1, o2, cnt;
        asm volatile("atom.relaxed.gpu.global.add.v4.f32 {%0,%1,%2,%3}, [%4], {%5,%6,%7,%8};"
                     : "=f"(o0), "=f"(o1), "=f"(o2), "=f"(cnt) : "l"(acc_dst), "f"(a0), "f"(a1), "f"(a2), "f"(1.0f) : "memory");
        CLK(ck3, __float_as_uint(cnt));
        if (cnt == 63.f) {
            int it = 0;
            while ((pkt_diff(gv, tag) & 3u) && ++it < POLL_MAX) gv = pkt_load(g_src);
            const uint32_t r01 = pack_bf16(xq[0] + bf16r(bf16r(o0 + a0) * pkt_f(gv.x)), xq[1] + bf16r(bf16r(o1 + a1) * pkt_f(gv.y)));
            const uint32_t r2 = pack_bf16(xq[2] + bf16r(bf16r(o2 + a2) * pkt_f(gv.z)), 0.f);
            unsigned short* dst = reinterpret_cast<unsigned short*>(out_dst);
            dst[0] = (unsigned short)r01;
            dst[8] = (unsigned short)(r01 >> 16);
            if (t4 < 2) dst[16] = (unsigned short)r2;
        }
    }
    if (tid == 0) STAMP(8);
}

typedef CUresult (*EncodeFn)(CUtensorMap*, CUtensorMapDataType, cuuint32_t, void*, const cuuint64_t*, const cuuint64_t*,
                             const cuuint32_t*, const cuuint32_t*, CUtensorMapInterleave, CUtensorMapSwizzle,
                             CUtensorMapL2promotion, CUtensorMapFloatOOBfill);

void make_map(EncodeFn enc, CUtensorMap* m, const void* ptr, uint64_t cols, uint64_t rows, uint64_t planes,
              uint32_t bc, uint32_t br, uint32_t bp, CUtensorMapSwizzle sw, int promo = 2) {
    cuuint64_t dims[3] = {cols, rows, planes};
    cuuint64_t strides[2] = {cols * 2, cols * rows * 2};
    cuuint32_t box[3] = {bc, br, bp};
    cuuint32_t es[3] = {1, 1, 1};
    enc(m, CU_TENSOR_MAP_DATA_TYPE_BFLOAT16, planes ? 3 : 2, const_cast<void*>(ptr), dims, strides, box, es,
        CU_TENSOR_MAP_INTERLEAVE_NONE, sw, (CUtensorMapL2promotion)promo, CU_TENSOR_MAP_FLOAT_OOB_FILL_NONE);
}

}

extern "C" void kernel_launch(void* const* d_in, const int* in_sizes, int n_in, void* d_out, int out_size) {
    (void)in_sizes; (void)n_in; (void)out_size;
    static EncodeFn enc = nullptr;
    static Scratch* scratch = nullptr;
    if (!enc) {
        void* fn = nullptr;
        cudaDriverEntryPointQueryResult qr;
        cudaGetDriverEntryPoint("cuTensorMapEncodeTiled", &fn, cudaEnableDefault, &qr);
        enc = (EncodeFn)fn;
        cudaGetSymbolAddress((void**)&scratch, g_scratch);
        cudaFuncSetAttribute(fused_decode_kernel, cudaFuncAttributeMaxDynamicSharedMemorySize, SMEM_BYTES);
    }
    Params p;
    p.k = (const uint8_t*)d_in[1];
    p.wq_raw = (const uint8_t*)d_in[3];
    p.wd_raw = (const uint8_t*)d_in[8];
    p.x = (const __nv_bfloat16*)d_in[0];
    p.out = (__nv_bfloat16*)d_out;
    p.sx = scratch;
    make_map(enc, &p.v,  d_in[2], 256,  (uint64_t)16 * SK, 0, 32, 256, 0, CU_TENSOR_MAP_SWIZZLE_64B, VPROMO);
    make_map(enc, &p.wq, d_in[3], 4096, D,    0,  64, 224, 0, CU_TENSOR_MAP_SWIZZLE_128B);
    {
        cuuint64_t dims[5] = {D, 16, 2, 8, 16};
        cuuint64_t strides[4] = {256 * D * 2, 8 * D * 2, D * 2, 16 * D * 2};
        cuuint32_t box[5] = {64, 2, 2, 8, 2};
        cuuint32_t es[5] = {1, 1, 1, 1, 1};
        CUresult r = enc(&p.wo, CU_TENSOR_MAP_DATA_TYPE_BFLOAT16, 5, d_in[4], dims, strides, box, es, CU_TENSOR_MAP_INTERLEAVE_NONE,
            CU_TENSOR_MAP_SWIZZLE_128B, CU_TENSOR_MAP_L2_PROMOTION_L2_128B, CU_TENSOR_MAP_FLOAT_OOB_FILL_NONE);
        (void)r;
    }
    make_map(enc, &p.wg, d_in[6], FF,   D,    0,  64, 224 / GUN, 0, CU_TENSOR_MAP_SWIZZLE_128B);
    make_map(enc, &p.wu, d_in[7], FF,   D,    0,  64, 224 / GUN, 0, CU_TENSOR_MAP_SWIZZLE_128B);
    make_map(enc, &p.wd, d_in[8], D,    FF,   0,  64, 128, 0, CU_TENSOR_MAP_SWIZZLE_128B);
    fused_decode_kernel<<<NCTA, NTHREADS, SMEM_BYTES, cudaStreamPerThread>>>(p);
}
```

```cpp
#include <cuda_runtime.h>
#include <cuda_bf16.h>
#include <cuda.h>
#include <stdint.h>

namespace {

constexpr int D = 448, SK = 32768, WIN = 4096, FF = 1792;
constexpr int NMAIN = 128, NHELP = 4, NCTA = NMAIN + NHELP;
constexpr int NS = 9;
constexpr int SLOT = 16384;
constexpr int NT = 16;
constexpr int NTHREADS = 288;

constexpr int KDEPTH = 3;
constexpr int VDEPTH = 2;
constexpr int NSTART = 2;
constexpr int GUPOS = 8;
constexpr int GUT = 10;
constexpr int WOPOS = 20;
constexpr int TWO = 13;
constexpr int TSTAT = 6;
constexpr int TPRE = 3;

__host__ __device__ constexpr int landed(int n) { return n < KDEPTH ? 0 : n < NT ? n - KDEPTH + 1 : n - VDEPTH + 1; }

constexpr int OFF_RING = 0;
constexpr int OFF_W    = OFF_RING + NS * SLOT;
constexpr int OFF_P    = OFF_W + 57344;
constexpr int P_PITCH  = WIN + 8;
constexpr int OFF_XN   = OFF_P + 2 * P_PITCH * 2;
constexpr int XN_PITCH = 456;
constexpr int OFF_Q    = OFF_XN + 2 * XN_PITCH * 2;
constexpr int OFF_ZERO = OFF_Q + 1024;
constexpr int OFF_PART = OFF_ZERO + 16;
constexpr int OFF_PART2 = OFF_PART + 2048;
constexpr int OFF_RED  = OFF_PART2 + 1024;
constexpr int OFF_TAG  = OFF_RED + 128;
constexpr int OFF_BAR  = OFF_TAG + 16;
constexpr int BAR_FULL = OFF_BAR, BAR_EMPTY = BAR_FULL + NS * 8;
constexpr int BAR_WQ = BAR_EMPTY + NS * 8, BAR_GU = BAR_WQ + 8, BAR_WO = BAR_GU + 8, BAR_WFREE = BAR_WO + 7 * 8;
constexpr int SMEM_BYTES = BAR_WFREE + 8 + 1024;
constexpr int H_PITCH = FF + 8;
static_assert(OFF_XN % 16 == 0 && OFF_Q % 16 == 0 && OFF_P % 16 == 0 && OFF_PART % 16 == 0 && OFF_BAR % 8 == 0, "align");
static_assert(SMEM_BYTES <= 232448, "smem");

struct __align__(4096) Scratch {
    float4 acc[2][2][256];
    uint4 sc[16 * 2048];
    uint4 q[NMAIN * 32];
    uint4 h[112 * 32];
    uint4 g[2 * 7 * 32];
    unsigned epoch[NCTA];
};
__device__ Scratch g_scratch;

struct Params {
    const uint8_t* wq_raw;
    const uint8_t* k;
    const __nv_bfloat16* x;
    __nv_bfloat16* out;
    Scratch* sx;
    alignas(64) CUtensorMap wq;
    CUtensorMap v, wg, wu, wo, wd;
};


__device__ __forceinline__ uint32_t smem_u32(const void* p) { return (uint32_t)__cvta_generic_to_shared(p); }
__device__ __forceinline__ bool elect_one() {
    uint32_t p;
    asm volatile("{\n.reg .pred P;\nelect.sync _|P, 0xffffffff;\nselp.u32 %0, 1, 0, P;\n}" : "=r"(p));
    return p;
}
__device__ __forceinline__ void mbar_init(uint32_t bar, uint32_t cnt) {
    asm volatile("mbarrier.init.shared::cta.b64 [%0], %1;" :: "r"(bar), "r"(cnt) : "memory");
}
__device__ __forceinline__ void mbar_expect_tx(uint32_t bar, uint32_t bytes) {
    asm volatile("mbarrier.arrive.expect_tx.shared::cta.b64 _, [%0], %1;" :: "r"(bar), "r"(bytes) : "memory");
}
__device__ __forceinline__ void mbar_arrive(uint32_t bar, uint32_t cnt) {
    asm volatile("mbarrier.arrive.shared::cta.b64 _, [%0], %1;" :: "r"(bar), "r"(cnt) : "memory");
}
__device__ __forceinline__ void mbar_wait(uint32_t bar, uint32_t parity) {
    uint32_t ok;
    int it = 0;
    do {
        asm volatile("{\n.reg .pred p;\nmbarrier.test_wait.parity.shared::cta.b64 p, [%1], %2;\nselp.u32 %0, 1, 0, p;\n}"
                     : "=r"(ok) : "r"(bar), "r"(parity) : "memory");
    } while (!ok && ++it < (1 << 24));
}
__device__ __forceinline__ void l2_prefetch(const void* src, uint32_t bytes) {
    asm volatile("cp.async.bulk.prefetch.L2.global [%0], %1;" :: "l"(src), "r"(bytes) : "memory");
}
__device__ __forceinline__ void bulk1d(uint32_t dst, const void* src, uint32_t bytes, uint32_t bar, uint64_t pol) {
    asm volatile("cp.async.bulk.shared::cluster.global.mbarrier::complete_tx::bytes.L2::cache_hint [%0], [%1], %2, [%3], %4;"
                 :: "r"(dst), "l"(src), "r"(bytes), "r"(bar), "l"(pol) : "memory");
}
__device__ __forceinline__ void tma2d(uint32_t dst, const CUtensorMap* map, int c0, int c1, uint32_t bar) {
    asm volatile("cp.async.bulk.tensor.2d.shared::cluster.global.mbarrier::complete_tx::bytes [%0], [%1, {%3, %4}], [%2];"
                 :: "r"(dst), "l"(map), "r"(bar), "r"(c0), "r"(c1) : "memory");
}
__device__ __forceinline__ void tma2d_hint(uint32_t dst, const CUtensorMap* map, int c0, int c1, uint32_t bar, uint64_t pol) {
    asm volatile("cp.async.bulk.tensor.2d.shared::cluster.global.mbarrier::complete_tx::bytes.L2::cache_hint [%0], [%1, {%3, %4}], [%2], %5;"
                 :: "r"(dst), "l"(map), "r"(bar), "r"(c0), "r"(c1), "l"(pol) : "memory");
}
__device__ __forceinline__ void tma5d(uint32_t dst, const CUtensorMap* map, int c0, int c1, int c4, uint32_t bar) {
    asm volatile("cp.async.bulk.tensor.5d.shared::cluster.global.mbarrier::complete_tx::bytes [%0], [%1, {%3, %4, %6, %6, %5}], [%2];"
                 :: "r"(dst), "l"(map), "r"(bar), "r"(c0), "r"(c1), "r"(c4), "r"(0) : "memory");
}
__device__ __forceinline__ void ldsm4(uint32_t (&r)[4], uint32_t addr) {
    asm volatile("ldmatrix.sync.aligned.m8n8.x4.shared.b16 {%0,%1,%2,%3}, [%4];"
                 : "=r"(r[0]), "=r"(r[1]), "=r"(r[2]), "=r"(r[3]) : "r"(addr) : "memory");
}
__device__ __forceinline__ void ldsm4t(uint32_t (&r)[4], uint32_t addr) {
    asm volatile("ldmatrix.sync.aligned.m8n8.x4.trans.shared.b16 {%0,%1,%2,%3}, [%4];"
                 : "=r"(r[0]), "=r"(r[1]), "=r"(r[2]), "=r"(r[3]) : "r"(addr) : "memory");
}
__device__ __forceinline__ void lds128(uint32_t (&r)[4], uint32_t addr) {
    asm volatile("ld.shared.v4.u32 {%0,%1,%2,%3}, [%4];"
                 : "=r"(r[0]), "=r"(r[1]), "=r"(r[2]), "=r"(r[3]) : "r"(addr) : "memory");
}
__device__ __forceinline__ void sts128_if(bool c, uint32_t addr, float x, float y, float z, float w) {
    asm volatile("{\n.reg .pred p;\nsetp.ne.u32 p, %5, 0;\n@p st.shared.v4.f32 [%0], {%1,%2,%3,%4};\n}"
                 :: "r"(addr), "f"(x), "f"(y), "f"(z), "f"(w), "r"((uint32_t)c) : "memory");
}
__device__ __forceinline__ float2 lds64(uint32_t addr) {
    float2 v;
    asm volatile("ld.shared.v2.f32 {%0,%1}, [%2];" : "=f"(v.x), "=f"(v.y) : "r"(addr) : "memory");
    return v;
}
#define PIN32(x) asm volatile("" : "+r"(x))
#define PIN64(x) asm volatile("" : "+l"(x))
__device__ __forceinline__ void mma16816(float (&c)[4], uint32_t a0, uint32_t a1, uint32_t a2, uint32_t a3, uint32_t b0, uint32_t b1) {
    asm volatile("mma.sync.aligned.m16n8k16.row.col.f32.bf16.bf16.f32 {%0,%1,%2,%3}, {%4,%5,%6,%7}, {%8,%9}, {%0,%1,%2,%3};"
                 : "+f"(c[0]), "+f"(c[1]), "+f"(c[2]), "+f"(c[3])
                 : "r"(a0), "r"(a1), "r"(a2), "r"(a3), "r"(b0), "r"(b1));
}
__device__ __forceinline__ void mma16816(float (&c)[4], const uint32_t (&a)[4], uint32_t b0, uint32_t b1) {
    mma16816(c, a[0], a[1], a[2], a[3], b0, b1);
}
__device__ __forceinline__ void bar_sync(int id, int n) { asm volatile("bar.sync %0, %1;" :: "r"(id), "r"(n) : "memory"); }
__device__ __forceinline__ void setup_barrier() { asm volatile("barrier.sync 3, %0;" :: "n"(NTHREADS) : "memory"); }
__device__ __forceinline__ void bar_arrive(int id, int n) { asm volatile("bar.arrive %0, %1;" :: "r"(id), "r"(n) : "memory"); }
__device__ __forceinline__ uint32_t pack_bf16(float lo, float hi) {
    uint32_t r;
    asm("cvt.rn.bf16x2.f32 %0, %1, %2;" : "=r"(r) : "f"(hi), "f"(lo));
    return r;
}
__device__ __forceinline__ float bf16r(float v) { return __uint_as_float(pack_bf16(0.f, v)); }

__device__ __forceinline__ float fsel(bool c, float a, float b) {
    float r;
    asm("{\n.reg .pred p;\nsetp.ne.u32 p, %3, 0;\nselp.f32 %0, %1, %2, p;\n}" : "=f"(r) : "f"(a), "f"(b), "r"((uint32_t)c));
    return r;
}

__device__ __forceinline__ __nv_bfloat16 geglu(float gate, float up) {
    const float ga = bf16r(gate);
    const float in = 0.7978845608028654f * (ga + 0.044715f * ga * ga * ga);
    return __float2bfloat16_rn(bf16r(0.5f * ga * (1.0f + tanhf(in))) * bf16r(up));
}

__device__ __forceinline__ void ldB(uint32_t (&r)[4], uint32_t base, int pitch_bytes, int k0, uint32_t zero, int lane) {
    const int n = lane & 7;
    ldsm4(r, n < 2 ? base + n * pitch_bytes + (k0 + 8 * (lane >> 3)) * 2 : zero);
}

__device__ __forceinline__ void pkt_store(uint4* p, float a, float b, float c, float d, uint32_t tag) {
    const uint32_t w0 = (__float_as_uint(a) & ~3u) | (tag & 3u);
    const uint32_t w1 = (__float_as_uint(b) & ~3u) | ((tag >> 2) & 3u);
    const uint32_t w2 = (__float_as_uint(c) & ~3u) | ((tag >> 4) & 3u);
    const uint32_t w3 = (__float_as_uint(d) & ~3u) | ((tag >> 6) & 3u);
    asm volatile("{\n.reg .b128 t;\n.reg .b64 lo, hi;\nmov.b64 lo, {%1, %2};\nmov.b64 hi, {%3, %4};\nmov.b128 t, {lo, hi};\n"
                 "st.relaxed.gpu.global.b128 [%0], t;\n}"
                 :: "l"(p), "r"(w0), "r"(w1), "r"(w2), "r"(w3) : "memory");
}
__device__ __forceinline__ void pkt_clear(uint4* p) { pkt_store(p, 0.f, 0.f, 0.f, 0.f, 0); }
__device__ __forceinline__ uint4 pkt_load(const uint4* p) {
    uint4 v;
    asm volatile("{\n.reg .b128 t;\n.reg .b64 lo, hi;\nld.relaxed.gpu.global.b128 t, [%4];\nmov.b128 {lo, hi}, t;\n"
                 "mov.b64 {%0, %1}, lo;\nmov.b64 {%2, %3}, hi;\n}"
                 : "=r"(v.x), "=r"(v.y), "=r"(v.z), "=r"(v.w) : "l"(p) : "memory");
    return v;
}
__device__ __forceinline__ uint32_t pkt_diff(const uint4& v, uint32_t tag) {
    return ((v.x ^ tag) | (v.y ^ (tag >> 2))) | ((v.z ^ (tag >> 4)) | (v.w ^ (tag >> 6)));
}
__device__ __forceinline__ float pkt_f(uint32_t w) { return __uint_as_float(w & ~3u); }
constexpr int POLL_MAX = 1 << 20;

__global__ void __launch_bounds__(NTHREADS, 1) fused_decode_kernel(const __grid_constant__ Params prm) {
    extern __shared__ uint8_t smem_raw[];
    const int cta = blockIdx.x;
    const int tid = threadIdx.x, lane = tid & 31;
    const bool is_main = cta < NMAIN;
    if (tid == 0 && is_main) l2_prefetch(prm.wq_raw + cta * 28672, 28672);
    const int warp = __shfl_sync(~0u, tid >> 5, 0);

    const uint32_t sb = (smem_u32(smem_raw) + 1023u) & ~1023u;
    const int grp = cta >> 3, j = cta & 7;
    const int b = grp >> 3;
    const bool has_ffn = is_main && j < 7;
    const int fblk = grp * 7 + j;
    const int qblk = (grp & 7) * 16 + b * 8 + j;
    const int ncg = is_main ? 0 : (cta - NMAIN < 3 ? 2 : 1);
    const int cg0 = (cta - NMAIN) * 2;
    Scratch* const sx = prm.sx;
    uint8_t* const sm = smem_raw + (sb - smem_u32(smem_raw));
    volatile uint32_t* const s_tag = reinterpret_cast<volatile uint32_t*>(sm + OFF_TAG);

    if (warp == 8) {
        const bool leader = elect_one();
        int ucta;
        asm volatile("mov.u32 %0, %%ctaid.x;" : "=r"(ucta));
        const uint8_t* const ksrc = prm.k + (uint32_t)(((ucta >> 3) * SK + (SK - WIN) + (ucta & 7) * 32) * 512);
        uint64_t pol;
        asm volatile("createpolicy.fractional.L2::evict_first.b64 %0, 1.0;" : "=l"(pol));
        if (leader) {
#pragma unroll
            for (int i = 0; i < NSTART; i++) mbar_init(sb + BAR_FULL + i * 8, 1);
            mbar_init(sb + BAR_WQ, 1);
            asm volatile("fence.mbarrier_init.release.cluster;" ::: "memory");
            if (is_main) {
                mbar_expect_tx(sb + BAR_WQ, 28672);
                tma2d(sb + OFF_W, &prm.wq, (qblk >> 1) * 64, (qblk & 1) * 224, sb + BAR_WQ);
#pragma unroll
                for (int i = 0; i < NSTART; i++) {
                    mbar_expect_tx(sb + BAR_FULL + i * 8, SLOT);
                    bulk1d(sb + OFF_RING + i * SLOT, ksrc + (size_t)i * 256 * 512, SLOT, sb + BAR_FULL + i * 8, pol);
                }
            }
#pragma unroll
            for (int i = NSTART; i < NS; i++) mbar_init(sb + BAR_FULL + i * 8, 1);
#pragma unroll
            for (int i = 0; i < NS; i++) mbar_init(sb + BAR_EMPTY + i * 8, 8);
            mbar_init(sb + BAR_GU, 1); mbar_init(sb + BAR_WFREE, 8);
#pragma unroll
            for (int c = 0; c < 7; c++) mbar_init(sb + BAR_WO + c * 8, 1);
            asm volatile("fence.mbarrier_init.release.cluster;" ::: "memory");
        }
        setup_barrier();
        if (is_main) {
            if (leader) {
                asm volatile("prefetch.tensormap [%0];" :: "l"((fblk & 1) ? &prm.wu : &prm.wg) : "memory");
                asm volatile("prefetch.tensormap [%0];" :: "l"(&prm.v) : "memory");
                asm volatile("prefetch.tensormap [%0];" :: "l"(&prm.wo) : "memory");
            }
            const int vrow = (ucta >> 3) * SK + (SK - WIN), vcol = (ucta & 7) * 32, wohead = ((ucta >> 3) & 7) * 2, woblk = (ucta & 7) * 2;
#pragma unroll
            for (int n = NSTART; n < 2 * NT; n++) {
                const uint32_t bar = sb + BAR_FULL + (n % NS) * 8, dst = sb + OFF_RING + (n % NS) * SLOT;
                if (n >= NS) mbar_wait(sb + BAR_EMPTY + (n % NS) * 8, (n / NS - 1) & 1);
                if (n == WOPOS) mbar_wait(sb + BAR_WFREE, 0);
                if (leader) {
                    mbar_expect_tx(bar, SLOT);
                    if (n == GUPOS && has_ffn) mbar_expect_tx(sb + BAR_GU, 28672);
                    if (n == WOPOS) {
#pragma unroll
                        for (int c = 0; c < 7; c++) mbar_expect_tx(sb + BAR_WO + c * 8, 8192);
                    }
                }
                const uint8_t* src = nullptr;
                int row = 0;
                if (n < NT) asm volatile("add.u64 %0, %1, %2;" : "=l"(src) : "l"(ksrc), "l"((uint64_t)n * 256 * 512));
                else        asm volatile("add.s32 %0, %1, %2;" : "=r"(row) : "r"(vrow), "r"((n - NT) * 256));
                if (n == NSTART) mbar_wait(sb + BAR_WQ, 0);
#pragma unroll
                for (int w = landed(n - 1); w < landed(n); w++) mbar_wait(sb + BAR_FULL + (w % NS) * 8, (w / NS) & 1);
                if (leader) {
                    if (n < NT) bulk1d(dst, src, SLOT, bar, pol);
                    else        tma2d_hint(dst, &prm.v, vcol, row, bar, pol);
                    if (n == GUPOS && has_ffn)
                        tma2d(sb + OFF_W + 28672, (fblk & 1) ? &prm.wu : &prm.wg, (fblk >> 2) * 64, ((fblk >> 1) & 1) * 224, sb + BAR_GU);
                    if (n >= WOPOS && n < WOPOS + 6)
                        tma5d(sb + OFF_W + (n - WOPOS) * 8192, &prm.wo, (n - WOPOS) * 64, wohead, woblk, sb + BAR_WO + (n - WOPOS) * 8);
                }
            }
            mbar_wait(sb + BAR_FULL + (30 % NS) * 8, (30 / NS) & 1);
            if (leader) tma5d(sb + OFF_W + 6 * 8192, &prm.wo, 6 * 64, wohead, woblk, sb + BAR_WO + 6 * 8);
            if (cta < 14) sx->acc[(s_tag[1] + 1) & 1][cta / 7][(cta % 7) * 32 + lane] = make_float4(0.f, 0.f, 0.f, 0.f);
        } else {
            int slot = 0, ph = 1;
            for (int n = 0; n < 14 * ncg; n++) {
                if (n >= NS) mbar_wait(sb + BAR_EMPTY + slot * 8, ph);
                if (leader) {
                    mbar_expect_tx(sb + BAR_FULL + slot * 8, SLOT);
                    tma2d(sb + OFF_RING + slot * SLOT, &prm.wd, (cg0 + (ncg == 2 ? (n & 1) : 0)) * 64, (ncg == 2 ? (n >> 1) : n) * 128,
                          sb + BAR_FULL + slot * 8);
                }
                if (++slot == NS) { slot = 0; ph ^= 1; }
            }
        }
        return;
    }

    const uint32_t zero = sb + OFF_ZERO;
    float* const s_part = reinterpret_cast<float*>(sm + OFF_PART);
    float* const s_red = reinterpret_cast<float*>(sm + OFF_RED);
    uint32_t xw[7];
    if (warp < 2 && is_main) {
        const uint32_t* xp = reinterpret_cast<const uint32_t*>(prm.x + warp * D);
#pragma unroll
        for (int i = 0; i < 7; i++) xw[i] = __ldg(xp + lane + 32 * i);
    }
    unsigned epoch = 0;
    if (tid == 64) epoch = sx->epoch[cta];
    if (tid == 96) *reinterpret_cast<uint4*>(sm + OFF_ZERO) = make_uint4(0, 0, 0, 0);
    if (is_main) {
        if (warp == 4) pkt_clear(&sx->q[qblk * 32 + lane]);
        if (warp == 5 && has_ffn) pkt_clear(&sx->h[fblk * 32 + lane]);
    } else if (warp < ncg * 2) {
        pkt_clear(&sx->g[((warp & 1) * 7 + cg0 + (warp >> 1)) * 32 + lane]);
    }
    setup_barrier();

    if (!is_main) {
        if (tid == 64) { sx->epoch[cta] = epoch + 1; s_tag[0] = epoch % 255u + 1u; }
        bar_sync(1, 256);
        const uint32_t tag = s_tag[0];
        __nv_bfloat16* h_s = reinterpret_cast<__nv_bfloat16*>(sm + OFF_W);
        {
            uint4 v[4][4];
            const int ncb = warp < 4 ? 4 : 3;
            int it = 0;
            uint32_t bad;
            do {
                if (it) __nanosleep(400);
                bad = 0;
#pragma unroll
                for (int i = 0; i < 4; i++)
#pragma unroll
                    for (int q = 0; q < 4; q++)
                        if (i < ncb) v[i][q] = pkt_load(&sx->h[(warp + 8 * i) * 128 + q * 32 + lane]);
#pragma unroll
                for (int i = 0; i < 4; i++)
                    if (i < ncb) bad |= (pkt_diff(v[i][0], tag) | pkt_diff(v[i][1], tag)) | (pkt_diff(v[i][2], tag) | pkt_diff(v[i][3], tag));
            } while ((bad & 3u) && ++it < POLL_MAX);
#pragma unroll
            for (int i = 0; i < 4; i++) {
                if (i < ncb) {
                    __nv_bfloat16* dst = h_s + (warp + 8 * i) * 64 + (lane >> 3) * 16 + (lane & 7);
                    dst[0]           = geglu(pkt_f(v[i][0].x) + pkt_f(v[i][2].x), pkt_f(v[i][1].x) + pkt_f(v[i][3].x));
                    dst[H_PITCH]     = geglu(pkt_f(v[i][0].y) + pkt_f(v[i][2].y), pkt_f(v[i][1].y) + pkt_f(v[i][3].y));
                    dst[8]           = geglu(pkt_f(v[i][0].z) + pkt_f(v[i][2].z), pkt_f(v[i][1].z) + pkt_f(v[i][3].z));
                    dst[H_PITCH + 8] = geglu(pkt_f(v[i][0].w) + pkt_f(v[i][2].w), pkt_f(v[i][1].w) + pkt_f(v[i][3].w));
                }
            }
        }
        bar_sync(1, 256);
        const int mt = warp & 3, kh = warp >> 2;
        float acc[2][4] = {};
        int slot = 0, ph = 0;
        for (int rb = 0; rb < 14; rb++) {
            uint32_t bf[2][4];
            ldB(bf[0], sb + OFF_W, H_PITCH * 2, rb * 128 + kh * 64, zero, lane);
            ldB(bf[1], sb + OFF_W, H_PITCH * 2, rb * 128 + kh * 64 + 32, zero, lane);
#pragma unroll
            for (int ci = 0; ci < 2; ci++) {
                if (ci < ncg) {
                    mbar_wait(sb + BAR_FULL + slot * 8, ph);
                    const uint32_t base = sb + OFF_RING + slot * SLOT;
#pragma unroll
                    for (int ks = 0; ks < 4; ks++) {
                        const int row = kh * 64 + ks * 16 + (lane & 7) + 8 * (lane >> 4);
                        const int ch = 2 * mt + ((lane >> 3) & 1);
                        uint32_t a[4];
                        ldsm4t(a, base + row * 128 + ((ch ^ (row & 7)) << 4));
                        mma16816(acc[ci], a, bf[ks >> 1][(ks & 1) * 2], bf[ks >> 1][(ks & 1) * 2 + 1]);
                    }
                    __syncwarp();
                    if (lane == 0) mbar_arrive(sb + BAR_EMPTY + slot * 8, 1);
                    if (++slot == NS) { slot = 0; ph ^= 1; }
                }
            }
        }
        if ((lane & 3) == 0) {
#pragma unroll
            for (int ci = 0; ci < 2; ci++) {
                float* p = s_part + kh * 256 + ci * 128 + (mt * 16 + (lane >> 2)) * 2;
                p[0] = acc[ci][0]; p[1] = acc[ci][1]; p[16] = acc[ci][2]; p[17] = acc[ci][3];
            }
        }
        bar_sync(1, 256);
        if (warp < ncg * 2) {
            const int ci = warp >> 1, bb = warp & 1;
            float g[3];
#pragma unroll
            for (int i = 0; i < 3; i++) {
                const int col = ((lane >> 2) + 8 * (3 * (lane & 3) + i)) & 63;
                const float y = bf16r(s_part[ci * 128 + col * 2 + bb] + s_part[256 + ci * 128 + col * 2 + bb]);
                g[i] = bf16r(y / (1.0f + expf(-y)));
            }
            pkt_store(&sx->g[(bb * 7 + cg0 + ci) * 32 + lane], g[0], g[1], g[2], 0.f, tag);
        }
        return;
    }

    if (warp < 2) {
        float xv[14], sum = 0.f;
#pragma unroll
        for (int i = 0; i < 7; i++) {
            xv[2 * i] = __uint_as_float(xw[i] << 16);
            xv[2 * i + 1] = __uint_as_float(xw[i] & 0xffff0000u);
            sum += xv[2 * i] + xv[2 * i + 1];
        }
#pragma unroll
        for (int o = 16; o; o >>= 1) sum += __shfl_xor_sync(~0u, sum, o);
        const float mean = sum * (1.0f / D);
        float var = 0.f;
#pragma unroll
        for (int i = 0; i < 14; i++) { const float d = xv[i] - mean; var += d * d; }
#pragma unroll
        for (int o = 16; o; o >>= 1) var += __shfl_xor_sync(~0u, var, o);
        const float mb = bf16r(mean);
        const float sd = bf16r(sqrtf(bf16r(bf16r(var * (1.0f / D)) + 1e-5f)));
        uint32_t* xn = reinterpret_cast<uint32_t*>(sm + OFF_XN + warp * XN_PITCH * 2);
#pragma unroll
        for (int i = 0; i < 7; i++) xn[lane + 32 * i] = pack_bf16(bf16r(xv[2 * i] - mb) / sd, bf16r(xv[2 * i + 1] - mb) / sd);
    }
    if (tid == 64) { sx->epoch[cta] = epoch + 1; s_tag[0] = epoch % 255u + 1u; s_tag[1] = epoch; }
    bar_sync(1, 256);
    const uint32_t tag = s_tag[0];
    float4* const acc_dst = &sx->acc[s_tag[1] & 1][b][warp * 32 + lane];

    auto project = [&](uint32_t wbase, int khalf, uint32_t bar, uint4* dst) {
        uint32_t xb[7][4];
#pragma unroll
        for (int i = 0; i < 7; i++) ldB(xb[i], sb + OFF_XN, XN_PITCH * 2, khalf * 224 + i * 32, zero, lane);
        float acc[2][4] = {};
        mbar_wait(bar, 0);
#pragma unroll
        for (int ks = 0; ks < 14; ks++) {
            const int row = ks * 16 + (lane & 7) + 8 * (lane >> 4);
            const int ch = 2 * (warp & 3) + ((lane >> 3) & 1);
            uint32_t a[4];
            ldsm4t(a, wbase + row * 128 + ((ch ^ (row & 7)) << 4));
            mma16816(acc[ks & 1], a, xb[ks >> 1][(ks & 1) * 2], xb[ks >> 1][(ks & 1) * 2 + 1]);
        }
        if ((lane & 3) == 0)
            pkt_store(dst + (warp & 3) * 8 + (lane >> 2), acc[0][0] + acc[1][0], acc[0][1] + acc[1][1], acc[0][2] + acc[1][2], acc[0][3] + acc[1][3], tag);
        __syncwarp();
        if (lane == 0) mbar_arrive(sb + BAR_WFREE, 1);
    };
    if (warp < 4) {
        project(sb + OFF_W, qblk & 1, sb + BAR_WQ, &sx->q[qblk * 32]);
    } else {
        if (!has_ffn && lane == 0) mbar_arrive(sb + BAR_WFREE, 1);
        mbar_wait(sb + BAR_WQ, 0);
    }
    {
        const uint4* src = &sx->q[((grp & 7) * 8 + warp) * 64 + lane];
        uint4 u, v;
        int it = 0;
        do { u = pkt_load(src); v = pkt_load(src + 32); } while (((pkt_diff(u, tag) | pkt_diff(v, tag)) & 3u) && ++it < POLL_MAX);
        __nv_bfloat16* dst = reinterpret_cast<__nv_bfloat16*>(sm + OFF_Q) + warp * 64 + (lane >> 3) * 16 + (lane & 7);
        dst[0] = __float2bfloat16_rn(pkt_f(b ? u.y : u.x) + pkt_f(b ? v.y : v.x));
        dst[8] = __float2bfloat16_rn(pkt_f(b ? u.w : u.z) + pkt_f(b ? v.w : v.z));
    }
    bar_sync(1, 256);

    const int pidx = ((lane >> 4) * 8 + warp) * 16 + (lane & 15);
    const uint4* const sc_src = &sx->sc[grp * 2048 + pidx];
    uint4 sv[4];
    {
        const int g = lane >> 2, t4 = lane & 3;
        uint32_t qb[8][4];
#pragma unroll
        for (int i = 0; i < 8; i++) lds128(qb[i], sb + OFF_Q + (g & 1) * 512 + ((i ^ ((g >> 1) & 1)) * 32 + t4 * 8) * 2);
        const int mt = warp & 1;
        const uint32_t roff = (mt * 16 + 2 * g) * 512 + t4 * 16;
        for (int t = 0; t < NT; t++) {
            const int slot = t % NS;
            if ((slot & 3) != (warp >> 1)) continue;
            if (t >= GUT && t < GUT + 4 && warp >= 4 && has_ffn) project(sb + OFF_W + 28672, (fblk >> 1) & 1, sb + BAR_GU, &sx->h[fblk * 32]);
            if (t >= NT - 4) {
#pragma unroll
                for (int i = 0; i < 4; i++) sv[i] = pkt_load(sc_src + i * 256);
            }
            mbar_wait(sb + BAR_FULL + slot * 8, (t / NS) & 1);
            const uint32_t base = sb + OFF_RING + slot * SLOT + roff;
            float acc0[4] = {}, acc1[4] = {};
#pragma unroll
            for (int i = 0; i < 8; i++) {
                uint32_t r0[4], r1[4];
                const uint32_t a = base + ((i ^ (g & 1)) << 6);
                lds128(r0, a);
                lds128(r1, a + 512);
                mma16816(acc0, r0[0], r1[0], r0[1], r1[1], qb[i][0], qb[i][1]);
                mma16816(acc1, r0[2], r1[2], r0[3], r1[3], qb[i][2], qb[i][3]);
            }
            __syncwarp();
            if (lane == 0) mbar_arrive(sb + BAR_EMPTY + slot * 8, 4);
            if (t4 == (g & 1)) {
                pkt_store(&sx->sc[grp * 2048 + ((t * 8 + j) * 2 + mt) * 8 + g],
                          bf16r(acc0[0] + acc1[0]) * 0.0625f, bf16r(acc0[2] + acc1[2]) * 0.0625f,
                          bf16r(acc0[1] + acc1[1]) * 0.0625f, bf16r(acc0[3] + acc1[3]) * 0.0625f, tag);
            }
        }
    }

    static_assert(landed(12) > NT - NS && VDEPTH <= KDEPTH && NS >= NT / 2 + 1 && TSTAT < NT / 2 + 1, "pipeline shape");
    const int ocol = b * D + warp * 64 + (lane >> 2) + 24 * ((lane & 3) < 3 ? (lane & 3) : 0);
    const uint4* const g_src = &sx->g[(b * 7 + warp) * 32 + lane];
    unsigned short* out_dst = reinterpret_cast<unsigned short*>(prm.out + ocol);
    uint32_t part_st = sb + OFF_PART2 + ((warp >> 1) * 64 + (warp & 1) * 32 + lane) * 4, part_ld = sb + OFF_PART2 + lane * 8;
    uint32_t wo_addr[4];
#pragma unroll
    for (int mt = 0; mt < 4; mt++) {
        const int row = (lane & 7) + 8 * (lane >> 4);
        wo_addr[mt] = sb + OFF_W + warp * 8192 + row * 128 + (((2 * mt + ((lane >> 3) & 1)) ^ (row & 7)) << 4);
        PIN32(wo_addr[mt]);
    }
    PIN64(out_dst); PIN32(part_st); PIN32(part_ld);
    uint4 gv;
    float xq[3];
    float oacc[2][4] = {};
    uint32_t wa[4][4][4];
    const int chb = (lane >> 3) & 1;
    {
        const float L2E = 1.4426950408889634f;
        uint32_t* const p0 = reinterpret_cast<uint32_t*>(sm + OFF_P) + pidx;
        uint32_t* const p1 = reinterpret_cast<uint32_t*>(sm + OFF_P + P_PITCH * 2) + pidx;
        float m0 = -INFINITY, m1 = -INFINITY, l0 = 0.f, l1 = 0.f, f0 = 1.f, f1 = 1.f;
        int slot = NT % NS, ph = (NT / NS) & 1;
        const int rowl = warp * 32 + (lane & 7) + 8 * (lane >> 4);
        const uint32_t voff = rowl * 64, vch0 = (chb ^ ((rowl >> 1) & 3)) << 4, vch1 = ((2 + chb) ^ ((rowl >> 1) & 3)) << 4;
#pragma unroll 1
        for (int t = 0; t < NT / 2; t++) {
            if (t == TSTAT - TPRE) {
#pragma unroll
                for (int i = 0; i < 4; i++) sv[i] = pkt_load(sc_src + (4 + i) * 256);
            }
            if (t == 0 || t == TSTAT) {
                const int i0 = t ? 4 : 0;
                int it = 0;
                while ((((pkt_diff(sv[0], tag) | pkt_diff(sv[1], tag)) | (pkt_diff(sv[2], tag) | pkt_diff(sv[3], tag))) & 3u) && ++it < POLL_MAX) {
#pragma unroll
                    for (int i = 0; i < 4; i++) sv[i] = pkt_load(sc_src + (i0 + i) * 256);
                }
                float e[4][4];
                float n0 = m0, n1 = m1;
#pragma unroll
                for (int i = 0; i < 4; i++) {
                    e[i][0] = pkt_f(sv[i].x); e[i][1] = pkt_f(sv[i].y); e[i][2] = pkt_f(sv[i].z); e[i][3] = pkt_f(sv[i].w);
                    n0 = fmaxf(n0, fmaxf(e[i][0], e[i][1])); n1 = fmaxf(n1, fmaxf(e[i][2], e[i][3]));
                }
#pragma unroll
                for (int o = 16; o; o >>= 1) {
                    n0 = fmaxf(n0, __shfl_xor_sync(~0u, n0, o));
                    n1 = fmaxf(n1, __shfl_xor_sync(~0u, n1, o));
                }
                l0 *= exp2f((m0 - n0) * L2E); l1 *= exp2f((m1 - n1) * L2E);
#pragma unroll
                for (int i = 0; i < 4; i++) {
                    e[i][0] = exp2f((e[i][0] - n0) * L2E); e[i][1] = exp2f((e[i][1] - n0) * L2E);
                    e[i][2] = exp2f((e[i][2] - n1) * L2E); e[i][3] = exp2f((e[i][3] - n1) * L2E);
                    l0 += e[i][0] + e[i][1]; l1 += e[i][2] + e[i][3];
                }
                float c0 = 1.f, c1 = 1.f;
                if (t) {
#pragma unroll
                    for (int o = 16; o; o >>= 1) {
                        l0 += __shfl_xor_sync(~0u, l0, o);
                        l1 += __shfl_xor_sync(~0u, l1, o);
                    }
                    if (lane == 0) *reinterpret_cast<float4*>(s_red + warp * 4) = make_float4(n0, l0, n1, l1);
                    bar_sync(1, 256);
                    const float4 st = *reinterpret_cast<const float4*>(s_red + (lane & 7) * 4);
                    float M0 = st.x, M1 = st.z;
#pragma unroll
                    for (int o = 4; o; o >>= 1) {
                        M0 = fmaxf(M0, __shfl_xor_sync(~0u, M0, o));
                        M1 = fmaxf(M1, __shfl_xor_sync(~0u, M1, o));
                    }
                    float L0 = st.y * exp2f((st.x - M0) * L2E), L1 = st.w * exp2f((st.z - M1) * L2E);
#pragma unroll
                    for (int o = 4; o; o >>= 1) {
                        L0 += __shfl_xor_sync(~0u, L0, o);
                        L1 += __shfl_xor_sync(~0u, L1, o);
                    }
                    c0 = exp2f((n0 - M0) * L2E) / L0; c1 = exp2f((n1 - M1) * L2E) / L1;
                    f0 = exp2f((m0 - M0) * L2E) / L0; f1 = exp2f((m1 - M1) * L2E) / L1;
                }
                m0 = n0; m1 = n1;
#pragma unroll
                for (int i = 0; i < 4; i++) {
                    p0[(i0 + i) * 256] = pack_bf16(e[i][0] * c0, e[i][1] * c0);
                    p1[(i0 + i) * 256] = pack_bf16(e[i][2] * c1, e[i][3] * c1);
                }
                __syncwarp();
            }
            uint32_t pb[4];
            ldB(pb, sb + OFF_P, P_PITCH * 2, t * 256 + warp * 32, zero, lane);
            mbar_wait(sb + BAR_FULL + slot * 8, ph);
            const uint32_t base = sb + OFF_RING + slot * SLOT + voff;
#pragma unroll
            for (int ks = 0; ks < 2; ks++) {
                uint32_t a0[4], a1[4];
                ldsm4t(a0, base + ks * 1024 + vch0);
                ldsm4t(a1, base + ks * 1024 + vch1);
                mma16816(oacc[0], a0, pb[ks * 2], pb[ks * 2 + 1]);
                mma16816(oacc[1], a1, pb[ks * 2], pb[ks * 2 + 1]);
            }
            __syncwarp();
            if (lane == 0) mbar_arrive(sb + BAR_EMPTY + slot * 8, 1);
            if (++slot == NS) { slot = 0; ph ^= 1; }
        }
        if ((lane & 3) == 0) {
#pragma unroll
            for (int mt = 0; mt < 2; mt++)
                *reinterpret_cast<float4*>(s_part + warp * 64 + mt * 32 + lane) =
                    make_float4(oacc[mt][0] * f0, oacc[mt][1] * f1, oacc[mt][2] * f0, oacc[mt][3] * f1);
        }
        bar_sync(1, 256);
        float o0[4] = {}, o1[4] = {}, o2[4] = {}, o3[4] = {};
        if ((lane & 3) == 0) {
            const float4 u = *reinterpret_cast<const float4*>(s_part + (warp & 6) * 64 + (warp & 1) * 32 + lane);
            const float4 v = *reinterpret_cast<const float4*>(s_part + (warp | 1) * 64 + (warp & 1) * 32 + lane);
            o0[0] = u.x; o0[1] = u.y; o0[2] = u.z; o0[3] = u.w;
            o1[0] = v.x; o1[1] = v.y; o1[2] = v.z; o1[3] = v.w;
        }
        const int row2 = (warp >> 1) * 64 + (lane & 7) + 8 * (lane >> 4);
        const uint32_t voff2 = row2 * 64 + (((2 * (warp & 1) + chb) ^ ((row2 >> 1) & 3)) << 4);
#pragma unroll
        for (int t = NT / 2; t < NT; t++) {
            if (t == TWO && warp < 7) {
                gv = pkt_load(g_src);
                const __nv_bfloat16* xp = prm.x + ocol;
                xq[0] = __bfloat162float(xp[0]); xq[1] = __bfloat162float(xp[8]); xq[2] = __bfloat162float(xp[(lane & 3) < 2 ? 16 : 0]);
            }
            if (t == TWO && warp < 6) {
                mbar_wait(sb + BAR_WO + warp * 8, 0);
#pragma unroll
                for (int ks = 0; ks < 4; ks++)
#pragma unroll
                    for (int mt = 0; mt < 4; mt++) ldsm4t(wa[mt][ks], wo_addr[mt] + ks * 2048);
            }
            uint32_t pb[2][4];
            ldB(pb[0], sb + OFF_P, P_PITCH * 2, t * 256 + (warp >> 1) * 64, zero, lane);
            ldB(pb[1], sb + OFF_P, P_PITCH * 2, t * 256 + (warp >> 1) * 64 + 32, zero, lane);
            mbar_wait(sb + BAR_FULL + ((NT + t) % NS) * 8, ((NT + t) / NS) & 1);
            const uint32_t base = sb + OFF_RING + ((NT + t) % NS) * SLOT + voff2;
            uint32_t a[4][4];
            ldsm4t(a[0], base); ldsm4t(a[1], base + 1024); ldsm4t(a[2], base + 2048); ldsm4t(a[3], base + 3072);
            mma16816(o0, a[0], pb[0][0], pb[0][1]);
            mma16816(o1, a[1], pb[0][2], pb[0][3]);
            mma16816(o2, a[2], pb[1][0], pb[1][1]);
            mma16816(o3, a[3], pb[1][2], pb[1][3]);
        }
        sts128_if((lane & 3) == 0, part_st, (o0[0] + o1[0]) + (o2[0] + o3[0]), (o0[1] + o1[1]) + (o2[1] + o3[1]),
                  (o0[2] + o1[2]) + (o2[2] + o3[2]), (o0[3] + o1[3]) + (o2[3] + o3[3]));
    }
    if (warp == 7) { bar_arrive(2, 256); return; }
    bar_sync(2, 256);
    const float2 v0 = lds64(part_ld), v1 = lds64(part_ld + 256), v2 = lds64(part_ld + 512), v3 = lds64(part_ld + 768);
    const uint32_t ow = pack_bf16((v0.x + v1.x) + (v2.x + v3.x), (v0.y + v1.y) + (v2.y + v3.y));
    if (warp == 6) {
        mbar_wait(sb + BAR_WO + warp * 8, 0);
#pragma unroll
        for (int ks = 0; ks < 4; ks++)
#pragma unroll
            for (int mt = 0; mt < 4; mt++) ldsm4t(wa[mt][ks], wo_addr[mt] + ks * 2048);
    }
    float acc[2][4][4] = {};
#pragma unroll
    for (int ks = 0; ks < 4; ks++) {
        const uint32_t b0 = __shfl_sync(~0u, ow, ks * 8 + (lane & 3));
        const uint32_t b1 = __shfl_sync(~0u, ow, ks * 8 + 4 + (lane & 3));
#pragma unroll
        for (int mt = 0; mt < 4; mt++) mma16816(acc[ks & 1][mt], wa[mt][ks], b0, b1);
    }
    const int t4 = lane & 3;
    float sum[8];
#pragma unroll
    for (int mt = 0; mt < 4; mt++) { sum[2 * mt] = acc[0][mt][0] + acc[1][mt][0]; sum[2 * mt + 1] = acc[0][mt][2] + acc[1][mt][2]; }
    const float a0 = fsel(t4 == 0, sum[0], fsel(t4 == 1, sum[3], sum[6]));
    const float a1 = fsel(t4 == 0, sum[1], fsel(t4 == 1, sum[4], sum[7]));
    const float a2 = fsel(t4 == 0, sum[2], fsel(t4 == 1, sum[5], 0.f));
    if (t4 < 3) {
        float o0, o1, o2, cnt;
        asm volatile("atom.relaxed.gpu.global.add.v4.f32 {%0,%1,%2,%3}, [%4], {%5,%6,%7,%8};"
                     : "=f"(o0), "=f"(o1), "=f"(o2), "=f"(cnt) : "l"(acc_dst), "f"(a0), "f"(a1), "f"(a2), "f"(1.0f) : "memory");
        if (cnt == 63.f) {
            int it = 0;
            while ((pkt_diff(gv, tag) & 3u) && ++it < POLL_MAX) gv = pkt_load(g_src);
            const uint32_t r01 = pack_bf16(xq[0] + bf16r(bf16r(o0 + a0) * pkt_f(gv.x)), xq[1] + bf16r(bf16r(o1 + a1) * pkt_f(gv.y)));
            const uint32_t r2 = pack_bf16(xq[2] + bf16r(bf16r(o2 + a2) * pkt_f(gv.z)), 0.f);
            asm volatile("st.global.u16 [%0], %1;" :: "l"(out_dst), "h"((unsigned short)r01) : "memory");
            asm volatile("st.global.u16 [%0+16], %1;" :: "l"(out_dst), "h"((unsigned short)(r01 >> 16)) : "memory");
            if (t4 < 2) asm volatile("st.global.u16 [%0+32], %1;" :: "l"(out_dst), "h"((unsigned short)r2) : "memory");
        }
    }
}

typedef CUresult (*EncodeFn)(CUtensorMap*, CUtensorMapDataType, cuuint32_t, void*, const cuuint64_t*, const cuuint64_t*,
                             const cuuint32_t*, const cuuint32_t*, CUtensorMapInterleave, CUtensorMapSwizzle,
                             CUtensorMapL2promotion, CUtensorMapFloatOOBfill);

void make_map(EncodeFn enc, CUtensorMap* m, const void* ptr, uint64_t cols, uint64_t rows, uint32_t bc, uint32_t br,
              CUtensorMapSwizzle sw) {
    cuuint64_t dims[2] = {cols, rows};
    cuuint64_t strides[1] = {cols * 2};
    cuuint32_t box[2] = {bc, br};
    cuuint32_t es[2] = {1, 1};
    enc(m, CU_TENSOR_MAP_DATA_TYPE_BFLOAT16, 2, const_cast<void*>(ptr), dims, strides, box, es,
        CU_TENSOR_MAP_INTERLEAVE_NONE, sw, CU_TENSOR_MAP_L2_PROMOTION_L2_128B, CU_TENSOR_MAP_FLOAT_OOB_FILL_NONE);
}

}

extern "C" void kernel_launch(void* const* d_in, const int* in_sizes, int n_in, void* d_out, int out_size) {
    (void)in_sizes; (void)n_in; (void)out_size;
    static EncodeFn enc = nullptr;
    static Scratch* scratch = nullptr;
    if (!enc) {
        void* fn = nullptr;
        cudaDriverEntryPointQueryResult qr;
        cudaGetDriverEntryPoint("cuTensorMapEncodeTiled", &fn, cudaEnableDefault, &qr);
        enc = (EncodeFn)fn;
        cudaGetSymbolAddress((void**)&scratch, g_scratch);
        cudaFuncSetAttribute(fused_decode_kernel, cudaFuncAttributeMaxDynamicSharedMemorySize, SMEM_BYTES);
    }
    Params p;
    p.k = (const uint8_t*)d_in[1];
    p.wq_raw = (const uint8_t*)d_in[3];
    p.x = (const __nv_bfloat16*)d_in[0];
    p.out = (__nv_bfloat16*)d_out;
    p.sx = scratch;
    make_map(enc, &p.v,  d_in[2], 256,  (uint64_t)16 * SK, 32, 256, CU_TENSOR_MAP_SWIZZLE_64B);
    make_map(enc, &p.wq, d_in[3], 4096, D,  64, 224, CU_TENSOR_MAP_SWIZZLE_128B);
    {
        cuuint64_t dims[5] = {D, 16, 2, 8, 16};
        cuuint64_t strides[4] = {256 * D * 2, 8 * D * 2, D * 2, 16 * D * 2};
        cuuint32_t box[5] = {64, 2, 2, 8, 2};
        cuuint32_t es[5] = {1, 1, 1, 1, 1};
        enc(&p.wo, CU_TENSOR_MAP_DATA_TYPE_BFLOAT16, 5, d_in[4], dims, strides, box, es, CU_TENSOR_MAP_INTERLEAVE_NONE,
            CU_TENSOR_MAP_SWIZZLE_128B, CU_TENSOR_MAP_L2_PROMOTION_L2_128B, CU_TENSOR_MAP_FLOAT_OOB_FILL_NONE);
    }
    make_map(enc, &p.wg, d_in[6], FF,   D,  64, 224, CU_TENSOR_MAP_SWIZZLE_128B);
    make_map(enc, &p.wu, d_in[7], FF,   D,  64, 224, CU_TENSOR_MAP_SWIZZLE_128B);
    make_map(enc, &p.wd, d_in[8], D,    FF, 64, 128, CU_TENSOR_MAP_SWIZZLE_128B);
    fused_decode_kernel<<<NCTA, NTHREADS, SMEM_BYTES, cudaStreamPerThread>>>(p);
}
```

```cpp
#include <cuda_runtime.h>
#include <cuda_bf16.h>
#include <cuda.h>
#include <stdint.h>

namespace {

constexpr int D = 448, SK = 32768, WIN = 4096, FF = 1792;
constexpr int NMAIN = 128, NHELP = 4, NCTA = NMAIN + NHELP;
constexpr int NS = 9;
constexpr int SLOT = 16384;
constexpr int NT = 16;
constexpr int NTHREADS = 288;

constexpr int MB = 4, NA = NT - MB;
constexpr int KDEPTH = 3;
constexpr int VDEPTH = 2;
constexpr int NSTART = 2;
constexpr int GUPOS = 8;
constexpr int GUT = 10;
constexpr int WOPOS = 20;
constexpr int TSC = 8, TSTAT = 10;
constexpr int TWO = 13;
constexpr int TO = 14;

__host__ __device__ constexpr int landed(int n) { return n < KDEPTH ? 0 : n < NT + NA ? n - KDEPTH + 1 : n - VDEPTH + 1; }

constexpr int OFF_RING = 0;
constexpr int OFF_W    = OFF_RING + NS * SLOT;
constexpr int OFF_P    = OFF_W + 57344;
constexpr int P_PITCH  = NA * 32 + MB * 256 + 8;
constexpr int OFF_SC   = OFF_P + 2 * P_PITCH * 2;
constexpr int OFF_XN   = OFF_SC + NA * 256;
constexpr int XN_PITCH = 456;
constexpr int OFF_Q    = OFF_XN + 2 * XN_PITCH * 2;
constexpr int OFF_ZERO = OFF_Q + 1024;
constexpr int OFF_PART = OFF_ZERO + 16;
constexpr int OFF_PART2 = OFF_PART + 2048;
constexpr int OFF_RED  = OFF_PART2 + 1024;
constexpr int OFF_TAG  = OFF_RED + 128;
constexpr int OFF_BAR  = OFF_TAG + 16;
constexpr int BAR_FULL = OFF_BAR, BAR_EMPTY = BAR_FULL + NS * 8;
constexpr int BAR_WQ = BAR_EMPTY + NS * 8, BAR_GU = BAR_WQ + 8, BAR_WO = BAR_GU + 8, BAR_WFREE = BAR_WO + 7 * 8;
constexpr int SMEM_BYTES = BAR_WFREE + 8 + 1024;
constexpr int H_PITCH = FF + 8;
static_assert(OFF_XN % 16 == 0 && OFF_Q % 16 == 0 && OFF_P % 16 == 0 && OFF_PART % 16 == 0 && OFF_BAR % 8 == 0, "align");
static_assert(SMEM_BYTES <= 232448, "smem");

struct __align__(4096) Scratch {
    float4 acc[2][2][256];
    uint4 sc[16 * MB * 128];
    uint4 o[NMAIN * 8 * 16];
    uint4 ml[NMAIN];
    uint4 q[NMAIN * 32];
    uint4 h[112 * 32];
    uint4 g[2 * 7 * 32];
    unsigned epoch[NCTA];
};
__device__ Scratch g_scratch;

struct Params {
    const uint8_t* wq_raw;
    const uint8_t* k;
    const __nv_bfloat16* x;
    __nv_bfloat16* out;
    Scratch* sx;
    alignas(64) CUtensorMap wq;
    CUtensorMap v, va, wg, wu, wo, wd;
};


__device__ __forceinline__ uint32_t smem_u32(const void* p) { return (uint32_t)__cvta_generic_to_shared(p); }
__device__ __forceinline__ bool elect_one() {
    uint32_t p;
    asm volatile("{\n.reg .pred P;\nelect.sync _|P, 0xffffffff;\nselp.u32 %0, 1, 0, P;\n}" : "=r"(p));
    return p;
}
__device__ __forceinline__ void mbar_init(uint32_t bar, uint32_t cnt) {
    asm volatile("mbarrier.init.shared::cta.b64 [%0], %1;" :: "r"(bar), "r"(cnt) : "memory");
}
__device__ __forceinline__ void mbar_expect_tx(uint32_t bar, uint32_t bytes) {
    asm volatile("mbarrier.arrive.expect_tx.shared::cta.b64 _, [%0], %1;" :: "r"(bar), "r"(bytes) : "memory");
}
__device__ __forceinline__ void mbar_arrive(uint32_t bar, uint32_t cnt) {
    asm volatile("mbarrier.arrive.shared::cta.b64 _, [%0], %1;" :: "r"(bar), "r"(cnt) : "memory");
}
__device__ __forceinline__ void mbar_wait(uint32_t bar, uint32_t parity) {
    uint32_t ok;
    int it = 0;
    do {
        asm volatile("{\n.reg .pred p;\nmbarrier.test_wait.parity.shared::cta.b64 p, [%1], %2;\nselp.u32 %0, 1, 0, p;\n}"
                     : "=r"(ok) : "r"(bar), "r"(parity) : "memory");
    } while (!ok && ++it < (1 << 24));
}
__device__ __forceinline__ void l2_prefetch(const void* src, uint32_t bytes) {
    asm volatile("cp.async.bulk.prefetch.L2.global [%0], %1;" :: "l"(src), "r"(bytes) : "memory");
}
__device__ __forceinline__ void bulk1d(uint32_t dst, const void* src, uint32_t bytes, uint32_t bar, uint64_t pol) {
    asm volatile("cp.async.bulk.shared::cluster.global.mbarrier::complete_tx::bytes.L2::cache_hint [%0], [%1], %2, [%3], %4;"
                 :: "r"(dst), "l"(src), "r"(bytes), "r"(bar), "l"(pol) : "memory");
}
__device__ __forceinline__ void tma2d(uint32_t dst, const CUtensorMap* map, int c0, int c1, uint32_t bar) {
    asm volatile("cp.async.bulk.tensor.2d.shared::cluster.global.mbarrier::complete_tx::bytes [%0], [%1, {%3, %4}], [%2];"
                 :: "r"(dst), "l"(map), "r"(bar), "r"(c0), "r"(c1) : "memory");
}
__device__ __forceinline__ void tma2d_hint(uint32_t dst, const CUtensorMap* map, int c0, int c1, uint32_t bar, uint64_t pol) {
    asm volatile("cp.async.bulk.tensor.2d.shared::cluster.global.mbarrier::complete_tx::bytes.L2::cache_hint [%0], [%1, {%3, %4}], [%2], %5;"
                 :: "r"(dst), "l"(map), "r"(bar), "r"(c0), "r"(c1), "l"(pol) : "memory");
}
__device__ __forceinline__ void tma3d_hint(uint32_t dst, const CUtensorMap* map, int c1, uint32_t bar, uint64_t pol) {
    asm volatile("cp.async.bulk.tensor.3d.shared::cluster.global.mbarrier::complete_tx::bytes.L2::cache_hint [%0], [%1, {%4, %3, %4}], [%2], %5;"
                 :: "r"(dst), "l"(map), "r"(bar), "r"(c1), "r"(0), "l"(pol) : "memory");
}
__device__ __forceinline__ void tma5d(uint32_t dst, const CUtensorMap* map, int c0, int c1, int c4, uint32_t bar, uint64_t pol) {
    asm volatile("cp.async.bulk.tensor.5d.shared::cluster.global.mbarrier::complete_tx::bytes.L2::cache_hint [%0], [%1, {%3, %4, %6, %6, %5}], [%2], %7;"
                 :: "r"(dst), "l"(map), "r"(bar), "r"(c0), "r"(c1), "r"(c4), "r"(0), "l"(pol) : "memory");
}
__device__ __forceinline__ void ldsm4(uint32_t (&r)[4], uint32_t addr) {
    asm volatile("ldmatrix.sync.aligned.m8n8.x4.shared.b16 {%0,%1,%2,%3}, [%4];"
                 : "=r"(r[0]), "=r"(r[1]), "=r"(r[2]), "=r"(r[3]) : "r"(addr) : "memory");
}
__device__ __forceinline__ void ldsm4t(uint32_t (&r)[4], uint32_t addr) {
    asm volatile("ldmatrix.sync.aligned.m8n8.x4.trans.shared.b16 {%0,%1,%2,%3}, [%4];"
                 : "=r"(r[0]), "=r"(r[1]), "=r"(r[2]), "=r"(r[3]) : "r"(addr) : "memory");
}
__device__ __forceinline__ void lds128(uint32_t (&r)[4], uint32_t addr) {
    asm volatile("ld.shared.v4.u32 {%0,%1,%2,%3}, [%4];"
                 : "=r"(r[0]), "=r"(r[1]), "=r"(r[2]), "=r"(r[3]) : "r"(addr) : "memory");
}
__device__ __forceinline__ void sts128_if(bool c, uint32_t addr, float x, float y, float z, float w) {
    asm volatile("{\n.reg .pred p;\nsetp.ne.u32 p, %5, 0;\n@p st.shared.v4.f32 [%0], {%1,%2,%3,%4};\n}"
                 :: "r"(addr), "f"(x), "f"(y), "f"(z), "f"(w), "r"((uint32_t)c) : "memory");
}
__device__ __forceinline__ float2 lds64(uint32_t addr) {
    float2 v;
    asm volatile("ld.shared.v2.f32 {%0,%1}, [%2];" : "=f"(v.x), "=f"(v.y) : "r"(addr) : "memory");
    return v;
}
#define PIN32(x) asm volatile("" : "+r"(x))
#define PIN64(x) asm volatile("" : "+l"(x))
__device__ __forceinline__ void mma16816(float (&c)[4], uint32_t a0, uint32_t a1, uint32_t a2, uint32_t a3, uint32_t b0, uint32_t b1) {
    asm volatile("mma.sync.aligned.m16n8k16.row.col.f32.bf16.bf16.f32 {%0,%1,%2,%3}, {%4,%5,%6,%7}, {%8,%9}, {%0,%1,%2,%3};"
                 : "+f"(c[0]), "+f"(c[1]), "+f"(c[2]), "+f"(c[3])
                 : "r"(a0), "r"(a1), "r"(a2), "r"(a3), "r"(b0), "r"(b1));
}
__device__ __forceinline__ void mma16816(float (&c)[4], const uint32_t (&a)[4], uint32_t b0, uint32_t b1) {
    mma16816(c, a[0], a[1], a[2], a[3], b0, b1);
}
__device__ __forceinline__ void bar_sync(int id, int n) { asm volatile("bar.sync %0, %1;" :: "r"(id), "r"(n) : "memory"); }
__device__ __forceinline__ void setup_barrier() { asm volatile("barrier.sync 3, %0;" :: "n"(NTHREADS) : "memory"); }
__device__ __forceinline__ void bar_arrive(int id, int n) { asm volatile("bar.arrive %0, %1;" :: "r"(id), "r"(n) : "memory"); }
__device__ __forceinline__ uint32_t pack_bf16(float lo, float hi) {
    uint32_t r;
    asm("cvt.rn.bf16x2.f32 %0, %1, %2;" : "=r"(r) : "f"(hi), "f"(lo));
    return r;
}
__device__ __forceinline__ float bf16r(float v) { return __uint_as_float(pack_bf16(0.f, v)); }

__device__ __forceinline__ float fsel(bool c, float a, float b) {
    float r;
    asm("{\n.reg .pred p;\nsetp.ne.u32 p, %3, 0;\nselp.f32 %0, %1, %2, p;\n}" : "=f"(r) : "f"(a), "f"(b), "r"((uint32_t)c));
    return r;
}

__device__ __forceinline__ __nv_bfloat16 geglu(float gate, float up) {
    const float ga = bf16r(gate);
    const float in = 0.7978845608028654f * (ga + 0.044715f * ga * ga * ga);
    return __float2bfloat16_rn(bf16r(0.5f * ga * (1.0f + tanhf(in))) * bf16r(up));
}

__device__ __forceinline__ void ldB(uint32_t (&r)[4], uint32_t base, int pitch_bytes, int k0, uint32_t zero, int lane) {
    const int n = lane & 7;
    ldsm4(r, n < 2 ? base + n * pitch_bytes + (k0 + 8 * (lane >> 3)) * 2 : zero);
}

__device__ __forceinline__ void pkt_store(uint4* p, float a, float b, float c, float d, uint32_t tag) {
    const uint32_t w0 = (__float_as_uint(a) & ~3u) | (tag & 3u);
    const uint32_t w1 = (__float_as_uint(b) & ~3u) | ((tag >> 2) & 3u);
    const uint32_t w2 = (__float_as_uint(c) & ~3u) | ((tag >> 4) & 3u);
    const uint32_t w3 = (__float_as_uint(d) & ~3u) | ((tag >> 6) & 3u);
    asm volatile("{\n.reg .b128 t;\n.reg .b64 lo, hi;\nmov.b64 lo, {%1, %2};\nmov.b64 hi, {%3, %4};\nmov.b128 t, {lo, hi};\n"
                 "st.relaxed.gpu.global.b128 [%0], t;\n}"
                 :: "l"(p), "r"(w0), "r"(w1), "r"(w2), "r"(w3) : "memory");
}
__device__ __forceinline__ void pkt_clear(uint4* p) { pkt_store(p, 0.f, 0.f, 0.f, 0.f, 0); }
__device__ __forceinline__ uint4 pkt_load(const uint4* p) {
    uint4 v;
    asm volatile("{\n.reg .b128 t;\n.reg .b64 lo, hi;\nld.relaxed.gpu.global.b128 t, [%4];\nmov.b128 {lo, hi}, t;\n"
                 "mov.b64 {%0, %1}, lo;\nmov.b64 {%2, %3}, hi;\n}"
                 : "=r"(v.x), "=r"(v.y), "=r"(v.z), "=r"(v.w) : "l"(p) : "memory");
    return v;
}
__device__ __forceinline__ uint32_t pkt_diff(const uint4& v, uint32_t tag) {
    return ((v.x ^ tag) | (v.y ^ (tag >> 2))) | ((v.z ^ (tag >> 4)) | (v.w ^ (tag >> 6)));
}
__device__ __forceinline__ float pkt_f(uint32_t w) { return __uint_as_float(w & ~3u); }
constexpr int POLL_MAX = 1 << 20;

__global__ void __launch_bounds__(NTHREADS, 1) fused_decode_kernel(const __grid_constant__ Params prm) {
    extern __shared__ uint8_t smem_raw[];
    const int cta = blockIdx.x;
    const int tid = threadIdx.x, lane = tid & 31;
    const bool is_main = cta < NMAIN;
    if (tid == 0 && is_main) {
        uint64_t pl; asm volatile("createpolicy.fractional.L2::evict_normal.b64 %0, 1.0;" : "=l"(pl));
        asm volatile("cp.async.bulk.prefetch.L2.global.L2::cache_hint [%0], %1, %2;" :: "l"(prm.wq_raw + cta * 28672), "r"(28672), "l"(pl) : "memory");
    }
    const int warp = __shfl_sync(~0u, tid >> 5, 0);

    const uint32_t sb = (smem_u32(smem_raw) + 1023u) & ~1023u;
    const int grp = cta >> 3, j = cta & 7;
    const int b = grp >> 3;
    const bool has_ffn = is_main && j < 7;
    const int fblk = grp * 7 + j;
    const int qblk = (grp & 7) * 16 + b * 8 + j;
    const int ncg = is_main ? 0 : (cta - NMAIN < 3 ? 2 : 1);
    const int cg0 = (cta - NMAIN) * 2;
    Scratch* const sx = prm.sx;
    uint8_t* const sm = smem_raw + (sb - smem_u32(smem_raw));
    volatile uint32_t* const s_tag = reinterpret_cast<volatile uint32_t*>(sm + OFF_TAG);

    if (warp == 8) {
        const bool leader = elect_one();
        int ucta;
        asm volatile("mov.u32 %0, %%ctaid.x;" : "=r"(ucta));
        const uint8_t* const ksrc = prm.k + (uint32_t)(((ucta >> 3) * SK + (SK - WIN) + (ucta & 7) * 32) * 512);
        uint64_t pol;
        asm volatile("createpolicy.fractional.L2::evict_first.b64 %0, 1.0;" : "=l"(pol));
        uint64_t npol;
        asm volatile("createpolicy.fractional.L2::evict_normal.b64 %0, 1.0;" : "=l"(npol));
        if (leader) {
#pragma unroll
            for (int i = 0; i < NSTART; i++) mbar_init(sb + BAR_FULL + i * 8, 1);
            mbar_init(sb + BAR_WQ, 1);
            asm volatile("fence.mbarrier_init.release.cluster;" ::: "memory");
            if (is_main) {
                mbar_expect_tx(sb + BAR_WQ, 28672);
                tma2d_hint(sb + OFF_W, &prm.wq, (qblk >> 1) * 64, (qblk & 1) * 224, sb + BAR_WQ, npol);
#pragma unroll
                for (int i = 0; i < NSTART; i++) {
                    mbar_expect_tx(sb + BAR_FULL + i * 8, SLOT);
                    bulk1d(sb + OFF_RING + i * SLOT, ksrc + (size_t)i * 256 * 512, SLOT, sb + BAR_FULL + i * 8, pol);
                }
            }
#pragma unroll
            for (int i = NSTART; i < NS; i++) mbar_init(sb + BAR_FULL + i * 8, 1);
#pragma unroll
            for (int i = 0; i < NS; i++) mbar_init(sb + BAR_EMPTY + i * 8, 8);
            mbar_init(sb + BAR_GU, 1); mbar_init(sb + BAR_WFREE, 8);
#pragma unroll
            for (int c = 0; c < 7; c++) mbar_init(sb + BAR_WO + c * 8, 1);
            asm volatile("fence.mbarrier_init.release.cluster;" ::: "memory");
        }
        setup_barrier();
        if (is_main) {
            if (leader) {
                asm volatile("prefetch.tensormap [%0];" :: "l"((fblk & 1) ? &prm.wu : &prm.wg) : "memory");
                asm volatile("prefetch.tensormap [%0];" :: "l"(&prm.va) : "memory");
                asm volatile("prefetch.tensormap [%0];" :: "l"(&prm.v) : "memory");
                asm volatile("prefetch.tensormap [%0];" :: "l"(&prm.wo) : "memory");
            }
            const int vrow = (ucta >> 3) * SK + (SK - WIN), vcol = (ucta & 7) * 32, wohead = ((ucta >> 3) & 7) * 2, woblk = (ucta & 7) * 2;
#pragma unroll
            for (int n = NSTART; n < 2 * NT; n++) {
                const uint32_t bar = sb + BAR_FULL + (n % NS) * 8, dst = sb + OFF_RING + (n % NS) * SLOT;
                if (n >= NS) mbar_wait(sb + BAR_EMPTY + (n % NS) * 8, (n / NS - 1) & 1);
                if (n == WOPOS) mbar_wait(sb + BAR_WFREE, 0);
                if (leader) {
                    mbar_expect_tx(bar, SLOT);
                    if (n == GUPOS && has_ffn) mbar_expect_tx(sb + BAR_GU, 28672);
                    if (n == WOPOS) {
#pragma unroll
                        for (int c = 0; c < 7; c++) mbar_expect_tx(sb + BAR_WO + c * 8, 8192);
                    }
                }
                const uint8_t* src = nullptr;
                int row = 0;
                if (n < NT) asm volatile("add.u64 %0, %1, %2;" : "=l"(src) : "l"(ksrc), "l"((uint64_t)n * 256 * 512));
                else        asm volatile("add.s32 %0, %1, %2;" : "=r"(row) : "r"(n < NT + NA ? vrow + vcol : vrow), "r"((n - NT) * 256));
                if (n == NSTART) mbar_wait(sb + BAR_WQ, 0);
#pragma unroll
                for (int w = landed(n - 1); w < landed(n); w++) mbar_wait(sb + BAR_FULL + (w % NS) * 8, (w / NS) & 1);
                if (leader) {
                    if (n < NT) bulk1d(dst, src, SLOT, bar, pol);
                    else if (n < NT + NA) tma3d_hint(dst, &prm.va, row, bar, pol);
                    else        tma2d_hint(dst, &prm.v, vcol, row, bar, pol);
                    if (n == GUPOS && has_ffn)
                        tma2d_hint(sb + OFF_W + 28672, (fblk & 1) ? &prm.wu : &prm.wg, (fblk >> 2) * 64, ((fblk >> 1) & 1) * 224, sb + BAR_GU, npol);
                    if (n >= WOPOS && n < WOPOS + 6)
                        tma5d(sb + OFF_W + (n - WOPOS) * 8192, &prm.wo, (n - WOPOS) * 64, wohead, woblk, sb + BAR_WO + (n - WOPOS) * 8, npol);
                }
            }
            mbar_wait(sb + BAR_FULL + (30 % NS) * 8, (30 / NS) & 1);
            if (leader) tma5d(sb + OFF_W + 6 * 8192, &prm.wo, 6 * 64, wohead, woblk, sb + BAR_WO + 6 * 8, npol);
            if (cta < 14) sx->acc[(s_tag[1] + 1) & 1][cta / 7][(cta % 7) * 32 + lane] = make_float4(0.f, 0.f, 0.f, 0.f);
        } else {
            int slot = 0, ph = 1;
            for (int n = 0; n < 14 * ncg; n++) {
                if (n >= NS) mbar_wait(sb + BAR_EMPTY + slot * 8, ph);
                if (leader) {
                    mbar_expect_tx(sb + BAR_FULL + slot * 8, SLOT);
                    tma2d_hint(sb + OFF_RING + slot * SLOT, &prm.wd, (cg0 + (ncg == 2 ? (n & 1) : 0)) * 64, (ncg == 2 ? (n >> 1) : n) * 128,
                          sb + BAR_FULL + slot * 8, npol);
                }
                if (++slot == NS) { slot = 0; ph ^= 1; }
            }
        }
        return;
    }

    const uint32_t zero = sb + OFF_ZERO;
    float* const s_part = reinterpret_cast<float*>(sm + OFF_PART);
    float* const s_red = reinterpret_cast<float*>(sm + OFF_RED);
    uint32_t xw[7];
    if (warp < 2 && is_main) {
        const uint32_t* xp = reinterpret_cast<const uint32_t*>(prm.x + warp * D);
#pragma unroll
        for (int i = 0; i < 7; i++) xw[i] = __ldg(xp + lane + 32 * i);
    }
    unsigned epoch = 0;
    if (tid == 64) epoch = sx->epoch[cta];
    if (tid == 96) *reinterpret_cast<uint4*>(sm + OFF_ZERO) = make_uint4(0, 0, 0, 0);
    if (is_main) {
        if (warp == 4) pkt_clear(&sx->q[qblk * 32 + lane]);
        if (warp == 5 && has_ffn) pkt_clear(&sx->h[fblk * 32 + lane]);
    } else if (warp < ncg * 2) {
        pkt_clear(&sx->g[((warp & 1) * 7 + cg0 + (warp >> 1)) * 32 + lane]);
    }
    setup_barrier();

    if (!is_main) {
        if (tid == 64) { sx->epoch[cta] = epoch + 1; s_tag[0] = epoch % 255u + 1u; }
        bar_sync(1, 256);
        const uint32_t tag = s_tag[0];
        __nv_bfloat16* h_s = reinterpret_cast<__nv_bfloat16*>(sm + OFF_W);
        {
            uint4 v[4][4];
            const int ncb = warp < 4 ? 4 : 3;
            int it = 0;
            uint32_t bad;
            do {
                if (it) __nanosleep(400);
                bad = 0;
#pragma unroll
                for (int i = 0; i < 4; i++)
#pragma unroll
                    for (int q = 0; q < 4; q++)
                        if (i < ncb) v[i][q] = pkt_load(&sx->h[(warp + 8 * i) * 128 + q * 32 + lane]);
#pragma unroll
                for (int i = 0; i < 4; i++)
                    if (i < ncb) bad |= (pkt_diff(v[i][0], tag) | pkt_diff(v[i][1], tag)) | (pkt_diff(v[i][2], tag) | pkt_diff(v[i][3], tag));
            } while ((bad & 3u) && ++it < POLL_MAX);
#pragma unroll
            for (int i = 0; i < 4; i++) {
                if (i < ncb) {
                    __nv_bfloat16* dst = h_s + (warp + 8 * i) * 64 + (lane >> 3) * 16 + (lane & 7);
                    dst[0]           = geglu(pkt_f(v[i][0].x) + pkt_f(v[i][2].x), pkt_f(v[i][1].x) + pkt_f(v[i][3].x));
                    dst[H_PITCH]     = geglu(pkt_f(v[i][0].y) + pkt_f(v[i][2].y), pkt_f(v[i][1].y) + pkt_f(v[i][3].y));
                    dst[8]           = geglu(pkt_f(v[i][0].z) + pkt_f(v[i][2].z), pkt_f(v[i][1].z) + pkt_f(v[i][3].z));
                    dst[H_PITCH + 8] = geglu(pkt_f(v[i][0].w) + pkt_f(v[i][2].w), pkt_f(v[i][1].w) + pkt_f(v[i][3].w));
                }
            }
        }
        bar_sync(1, 256);
        const int mt = warp & 3, kh = warp >> 2;
        float acc[2][4] = {};
        int slot = 0, ph = 0;
        for (int rb = 0; rb < 14; rb++) {
            uint32_t bf[2][4];
            ldB(bf[0], sb + OFF_W, H_PITCH * 2, rb * 128 + kh * 64, zero, lane);
            ldB(bf[1], sb + OFF_W, H_PITCH * 2, rb * 128 + kh * 64 + 32, zero, lane);
#pragma unroll
            for (int ci = 0; ci < 2; ci++) {
                if (ci < ncg) {
                    mbar_wait(sb + BAR_FULL + slot * 8, ph);
                    const uint32_t base = sb + OFF_RING + slot * SLOT;
#pragma unroll
                    for (int ks = 0; ks < 4; ks++) {
                        const int row = kh * 64 + ks * 16 + (lane & 7) + 8 * (lane >> 4);
                        const int ch = 2 * mt + ((lane >> 3) & 1);
                        uint32_t a[4];
                        ldsm4t(a, base + row * 128 + ((ch ^ (row & 7)) << 4));
                        mma16816(acc[ci], a, bf[ks >> 1][(ks & 1) * 2], bf[ks >> 1][(ks & 1) * 2 + 1]);
                    }
                    __syncwarp();
                    if (lane == 0) mbar_arrive(sb + BAR_EMPTY + slot * 8, 1);
                    if (++slot == NS) { slot = 0; ph ^= 1; }
                }
            }
        }
        if ((lane & 3) == 0) {
#pragma unroll
            for (int ci = 0; ci < 2; ci++) {
                float* p = s_part + kh * 256 + ci * 128 + (mt * 16 + (lane >> 2)) * 2;
                p[0] = acc[ci][0]; p[1] = acc[ci][1]; p[16] = acc[ci][2]; p[17] = acc[ci][3];
            }
        }
        bar_sync(1, 256);
        if (warp < ncg * 2) {
            const int ci = warp >> 1, bb = warp & 1;
            float g[3];
#pragma unroll
            for (int i = 0; i < 3; i++) {
                const int col = ((lane >> 2) + 8 * (3 * (lane & 3) + i)) & 63;
                const float y = bf16r(s_part[ci * 128 + col * 2 + bb] + s_part[256 + ci * 128 + col * 2 + bb]);
                g[i] = bf16r(y / (1.0f + expf(-y)));
            }
            pkt_store(&sx->g[(bb * 7 + cg0 + ci) * 32 + lane], g[0], g[1], g[2], 0.f, tag);
        }
        return;
    }

    if (warp < 2) {
        float xv[14], sum = 0.f;
#pragma unroll
        for (int i = 0; i < 7; i++) {
            xv[2 * i] = __uint_as_float(xw[i] << 16);
            xv[2 * i + 1] = __uint_as_float(xw[i] & 0xffff0000u);
            sum += xv[2 * i] + xv[2 * i + 1];
        }
#pragma unroll
        for (int o = 16; o; o >>= 1) sum += __shfl_xor_sync(~0u, sum, o);
        const float mean = sum * (1.0f / D);
        float var = 0.f;
#pragma unroll
        for (int i = 0; i < 14; i++) { const float d = xv[i] - mean; var += d * d; }
#pragma unroll
        for (int o = 16; o; o >>= 1) var += __shfl_xor_sync(~0u, var, o);
        const float mb = bf16r(mean);
        const float sd = bf16r(sqrtf(bf16r(bf16r(var * (1.0f / D)) + 1e-5f)));
        uint32_t* xn = reinterpret_cast<uint32_t*>(sm + OFF_XN + warp * XN_PITCH * 2);
#pragma unroll
        for (int i = 0; i < 7; i++) xn[lane + 32 * i] = pack_bf16(bf16r(xv[2 * i] - mb) / sd, bf16r(xv[2 * i + 1] - mb) / sd);
    }
    if (tid == 64) { sx->epoch[cta] = epoch + 1; s_tag[0] = epoch % 255u + 1u; s_tag[1] = epoch; }
    bar_sync(1, 256);
    const uint32_t tag = s_tag[0];
    float4* const acc_dst = &sx->acc[s_tag[1] & 1][b][warp * 32 + lane];

    auto project = [&](uint32_t wbase, int khalf, uint32_t bar, uint4* dst) {
        uint32_t xb[7][4];
#pragma unroll
        for (int i = 0; i < 7; i++) ldB(xb[i], sb + OFF_XN, XN_PITCH * 2, khalf * 224 + i * 32, zero, lane);
        float acc[2][4] = {};
        mbar_wait(bar, 0);
#pragma unroll
        for (int ks = 0; ks < 14; ks++) {
            const int row = ks * 16 + (lane & 7) + 8 * (lane >> 4);
            const int ch = 2 * (warp & 3) + ((lane >> 3) & 1);
            uint32_t a[4];
            ldsm4t(a, wbase + row * 128 + ((ch ^ (row & 7)) << 4));
            mma16816(acc[ks & 1], a, xb[ks >> 1][(ks & 1) * 2], xb[ks >> 1][(ks & 1) * 2 + 1]);
        }
        if ((lane & 3) == 0)
            pkt_store(dst + (warp & 3) * 8 + (lane >> 2), acc[0][0] + acc[1][0], acc[0][1] + acc[1][1], acc[0][2] + acc[1][2], acc[0][3] + acc[1][3], tag);
        __syncwarp();
        if (lane == 0) mbar_arrive(sb + BAR_WFREE, 1);
    };
    if (warp < 4) {
        project(sb + OFF_W, qblk & 1, sb + BAR_WQ, &sx->q[qblk * 32]);
    } else {
        if (!has_ffn && lane == 0) mbar_arrive(sb + BAR_WFREE, 1);
        mbar_wait(sb + BAR_WQ, 0);
    }
    {
        const uint4* src = &sx->q[((grp & 7) * 8 + warp) * 64 + lane];
        uint4 u, v;
        int it = 0;
        do { u = pkt_load(src); v = pkt_load(src + 32); } while (((pkt_diff(u, tag) | pkt_diff(v, tag)) & 3u) && ++it < POLL_MAX);
        __nv_bfloat16* dst = reinterpret_cast<__nv_bfloat16*>(sm + OFF_Q) + warp * 64 + (lane >> 3) * 16 + (lane & 7);
        dst[0] = __float2bfloat16_rn(pkt_f(b ? u.y : u.x) + pkt_f(b ? v.y : v.x));
        dst[8] = __float2bfloat16_rn(pkt_f(b ? u.w : u.z) + pkt_f(b ? v.w : v.z));
    }
    bar_sync(1, 256);

    {
        const int g = lane >> 2, t4 = lane & 3;
        uint32_t qb[8][4];
#pragma unroll
        for (int i = 0; i < 8; i++) lds128(qb[i], sb + OFF_Q + (g & 1) * 512 + ((i ^ ((g >> 1) & 1)) * 32 + t4 * 8) * 2);
        const int mt = warp & 1;
        const uint32_t roff = (mt * 16 + 2 * g) * 512 + t4 * 16;
        for (int t = 0; t < NT; t++) {
            const int slot = t % NS;
            if ((slot & 3) != (warp >> 1)) continue;
            if (t >= GUT && t < GUT + 4 && warp >= 4 && has_ffn) project(sb + OFF_W + 28672, (fblk >> 1) & 1, sb + BAR_GU, &sx->h[fblk * 32]);
            mbar_wait(sb + BAR_FULL + slot * 8, (t / NS) & 1);
            const uint32_t base = sb + OFF_RING + slot * SLOT + roff;
            float acc0[4] = {}, acc1[4] = {};
#pragma unroll
            for (int i = 0; i < 8; i++) {
                uint32_t r0[4], r1[4];
                const uint32_t a = base + ((i ^ (g & 1)) << 6);
                lds128(r0, a);
                lds128(r1, a + 512);
                mma16816(acc0, r0[0], r1[0], r0[1], r1[1], qb[i][0], qb[i][1]);
                mma16816(acc1, r0[2], r1[2], r0[3], r1[3], qb[i][2], qb[i][3]);
            }
            __syncwarp();
            if (lane == 0) mbar_arrive(sb + BAR_EMPTY + slot * 8, 4);
            const float s0 = bf16r(acc0[0] + acc1[0]) * 0.0625f, s1 = bf16r(acc0[2] + acc1[2]) * 0.0625f;
            const float s2 = bf16r(acc0[1] + acc1[1]) * 0.0625f, s3 = bf16r(acc0[3] + acc1[3]) * 0.0625f;
            if (t < NA) sts128_if(t4 == (g & 1), sb + OFF_SC + ((t * 2 + mt) * 8 + g) * 16, s0, s1, s2, s3);
            else if (t4 == (g & 1)) pkt_store(&sx->sc[grp * MB * 128 + (((t - NA) * 8 + j) * 2 + mt) * 8 + g], s0, s1, s2, s3, tag);
        }
    }

    static_assert(VDEPTH <= KDEPTH && MB % 2 == 0 && TSC < TSTAT && TSTAT < NA && TWO >= NA && TO >= NA && NS > MB, "pipeline shape");
    const int ocol = b * D + warp * 64 + (lane >> 2) + 24 * ((lane & 3) < 3 ? (lane & 3) : 0);
    const uint4* const g_src = &sx->g[(b * 7 + warp) * 32 + lane];
    unsigned short* out_dst = reinterpret_cast<unsigned short*>(prm.out + ocol);
    uint32_t part_st = sb + OFF_PART2 + ((warp >> 1) * 64 + (warp & 1) * 32 + lane) * 4, part_ld = sb + OFF_PART2 + lane * 8;
    uint32_t wo_addr[4];
#pragma unroll
    for (int mt = 0; mt < 4; mt++) {
        const int row = (lane & 7) + 8 * (lane >> 4);
        wo_addr[mt] = sb + OFF_W + warp * 8192 + row * 128 + (((2 * mt + ((lane >> 3) & 1)) ^ (row & 7)) << 4);
        PIN32(wo_addr[mt]);
    }
    PIN64(out_dst); PIN32(part_st); PIN32(part_ld);
    uint4 gv;
    float xq[3];
    float oacc[2][4] = {};
    uint32_t wa[4][4][4];
    const int chb = (lane >> 3) & 1;
    {
        const float L2E = 1.4426950408889634f;
        uint32_t* const p0 = reinterpret_cast<uint32_t*>(sm + OFF_P);
        uint32_t* const p1 = reinterpret_cast<uint32_t*>(sm + OFF_P + P_PITCH * 2);
        uint4* const o_dst = &sx->o[((grp * 8 + warp) * 8 + j) * 16 + (lane >> 2)];
        if ((lane & 3) == 0) { pkt_clear(o_dst); pkt_clear(o_dst + 8); }
        float m0, m1, f0 = 1.f, f1 = 1.f;
        bar_sync(1, 256);
        {
            constexpr int NP = NA / 2;
            float e[NP][4];
#pragma unroll
            for (int i = 0; i < NP; i++) {
                const float4 v = *reinterpret_cast<const float4*>(sm + OFF_SC + (i * 32 + lane) * 16);
                e[i][0] = v.x; e[i][1] = v.y; e[i][2] = v.z; e[i][3] = v.w;
            }
            m0 = fmaxf(e[0][0], e[0][1]); m1 = fmaxf(e[0][2], e[0][3]);
#pragma unroll
            for (int i = 1; i < NP; i++) { m0 = fmaxf(m0, fmaxf(e[i][0], e[i][1])); m1 = fmaxf(m1, fmaxf(e[i][2], e[i][3])); }
#pragma unroll
            for (int o = 16; o; o >>= 1) {
                m0 = fmaxf(m0, __shfl_xor_sync(~0u, m0, o));
                m1 = fmaxf(m1, __shfl_xor_sync(~0u, m1, o));
            }
            float l0 = 0.f, l1 = 0.f;
#pragma unroll
            for (int i = 0; i < NP; i++) {
                e[i][0] = exp2f((e[i][0] - m0) * L2E); e[i][1] = exp2f((e[i][1] - m0) * L2E);
                e[i][2] = exp2f((e[i][2] - m1) * L2E); e[i][3] = exp2f((e[i][3] - m1) * L2E);
                l0 += e[i][0] + e[i][1]; l1 += e[i][2] + e[i][3];
                if (i == warp) { p0[i * 32 + lane] = pack_bf16(e[i][0], e[i][1]); p1[i * 32 + lane] = pack_bf16(e[i][2], e[i][3]); }
            }
            if (warp == 7) {
#pragma unroll
                for (int o = 16; o; o >>= 1) {
                    l0 += __shfl_xor_sync(~0u, l0, o);
                    l1 += __shfl_xor_sync(~0u, l1, o);
                }
                if (lane == 0) pkt_store(&sx->ml[cta], m0, l0, m1, l1, tag);
            }
        }
        bar_sync(1, 256);
        constexpr int NB = MB / 2;
        const uint4* const sc_src = &sx->sc[grp * MB * 128 + tid];
        const uint4* const ml_src = &sx->ml[grp * 8 + (lane & 7)];
        uint4 sv[NB], mv;
        int slot = NT % NS, ph = (NT / NS) & 1;
        const int rowl = (lane & 7) + 8 * (lane >> 4);
        const uint32_t voff = (warp >> 1) * 4096 + rowl * 128;
        const uint32_t vch0 = (((warp & 1) * 4 + chb) ^ (rowl & 7)) << 4, vch1 = (((warp & 1) * 4 + 2 + chb) ^ (rowl & 7)) << 4;
#pragma unroll 1
        for (int t = 0; t < NA; t++) {
            if (t == TSC) {
#pragma unroll
                for (int i = 0; i < NB; i++) sv[i] = pkt_load(sc_src + i * 256);
                mv = pkt_load(ml_src);
            }
            if (t == TSTAT) {
                int it = 0;
                for (;;) {
                    uint32_t bad = pkt_diff(mv, tag);
#pragma unroll
                    for (int i = 0; i < NB; i++) bad |= pkt_diff(sv[i], tag);
                    if (!(bad & 3u) || ++it >= POLL_MAX) break;
#pragma unroll
                    for (int i = 0; i < NB; i++) sv[i] = pkt_load(sc_src + i * 256);
                    mv = pkt_load(ml_src);
                }
                float e[NB][4];
                float n0 = -INFINITY, n1 = -INFINITY, l0 = 0.f, l1 = 0.f;
#pragma unroll
                for (int i = 0; i < NB; i++) {
                    e[i][0] = pkt_f(sv[i].x); e[i][1] = pkt_f(sv[i].y); e[i][2] = pkt_f(sv[i].z); e[i][3] = pkt_f(sv[i].w);
                    n0 = fmaxf(n0, fmaxf(e[i][0], e[i][1])); n1 = fmaxf(n1, fmaxf(e[i][2], e[i][3]));
                }
#pragma unroll
                for (int o = 16; o; o >>= 1) {
                    n0 = fmaxf(n0, __shfl_xor_sync(~0u, n0, o));
                    n1 = fmaxf(n1, __shfl_xor_sync(~0u, n1, o));
                }
#pragma unroll
                for (int i = 0; i < NB; i++) {
                    e[i][0] = exp2f((e[i][0] - n0) * L2E); e[i][1] = exp2f((e[i][1] - n0) * L2E);
                    e[i][2] = exp2f((e[i][2] - n1) * L2E); e[i][3] = exp2f((e[i][3] - n1) * L2E);
                    l0 += e[i][0] + e[i][1]; l1 += e[i][2] + e[i][3];
                }
#pragma unroll
                for (int o = 16; o; o >>= 1) {
                    l0 += __shfl_xor_sync(~0u, l0, o);
                    l1 += __shfl_xor_sync(~0u, l1, o);
                }
                if (lane == 0) *reinterpret_cast<float4*>(s_red + warp * 4) = make_float4(n0, l0, n1, l1);
                bar_sync(1, 256);
                float4 st = *reinterpret_cast<const float4*>(s_red + (lane & 7) * 4);
                if (lane & 8) st = make_float4(pkt_f(mv.x), pkt_f(mv.y), pkt_f(mv.z), pkt_f(mv.w));
                float M0 = st.x, M1 = st.z;
#pragma unroll
                for (int o = 8; o; o >>= 1) {
                    M0 = fmaxf(M0, __shfl_xor_sync(~0u, M0, o));
                    M1 = fmaxf(M1, __shfl_xor_sync(~0u, M1, o));
                }
                float L0 = st.y * exp2f((st.x - M0) * L2E), L1 = st.w * exp2f((st.z - M1) * L2E);
#pragma unroll
                for (int o = 8; o; o >>= 1) {
                    L0 += __shfl_xor_sync(~0u, L0, o);
                    L1 += __shfl_xor_sync(~0u, L1, o);
                }
                const float c0 = exp2f((n0 - M0) * L2E) / L0, c1 = exp2f((n1 - M1) * L2E) / L1;
                f0 = exp2f((m0 - M0) * L2E) / L0; f1 = exp2f((m1 - M1) * L2E) / L1;
#pragma unroll
                for (int i = 0; i < NB; i++) {
                    p0[NA * 16 + i * 256 + tid] = pack_bf16(e[i][0] * c0, e[i][1] * c0);
                    p1[NA * 16 + i * 256 + tid] = pack_bf16(e[i][2] * c1, e[i][3] * c1);
                }
            }
            uint32_t pb[4];
            ldB(pb, sb + OFF_P, P_PITCH * 2, t * 32, zero, lane);
            mbar_wait(sb + BAR_FULL + slot * 8, ph);
            const uint32_t base = sb + OFF_RING + slot * SLOT + voff;
#pragma unroll
            for (int ks = 0; ks < 2; ks++) {
                uint32_t a0[4], a1[4];
                ldsm4t(a0, base + ks * 2048 + vch0);
                ldsm4t(a1, base + ks * 2048 + vch1);
                mma16816(oacc[0], a0, pb[ks * 2], pb[ks * 2 + 1]);
                mma16816(oacc[1], a1, pb[ks * 2], pb[ks * 2 + 1]);
            }
            __syncwarp();
            if (lane == 0) mbar_arrive(sb + BAR_EMPTY + slot * 8, 1);
            if (++slot == NS) { slot = 0; ph ^= 1; }
        }
        if ((lane & 3) == 0) {
            pkt_store(o_dst, oacc[0][0] * f0, oacc[0][1] * f1, oacc[0][2] * f0, oacc[0][3] * f1, tag);
            pkt_store(o_dst + 8, oacc[1][0] * f0, oacc[1][1] * f1, oacc[1][2] * f0, oacc[1][3] * f1, tag);
        }
        bar_sync(1, 256);
        float o0[4] = {}, o1[4] = {}, o2[4] = {}, o3[4] = {};
        const uint4* const o_src = &sx->o[(cta * 8 + (warp & 6)) * 16 + (warp & 1) * 8 + (lane >> 2)];
        uint4 oa, ob;
        const int row2 = (warp >> 1) * 64 + (lane & 7) + 8 * (lane >> 4);
        const uint32_t voff2 = row2 * 64 + (((2 * (warp & 1) + chb) ^ ((row2 >> 1) & 3)) << 4);
#pragma unroll
        for (int t = NA; t < NT; t++) {
            if (t == TO) { oa = pkt_load(o_src); ob = pkt_load(o_src + 16); }
            if (t == NT - 1) {
                int it = 0;
                while (((pkt_diff(oa, tag) | pkt_diff(ob, tag)) & 3u) && ++it < POLL_MAX) { oa = pkt_load(o_src); ob = pkt_load(o_src + 16); }
                o0[0] += pkt_f(oa.x); o0[1] += pkt_f(oa.y); o0[2] += pkt_f(oa.z); o0[3] += pkt_f(oa.w);
                o1[0] += pkt_f(ob.x); o1[1] += pkt_f(ob.y); o1[2] += pkt_f(ob.z); o1[3] += pkt_f(ob.w);
            }
            if (t == TWO && warp < 7) {
                gv = pkt_load(g_src);
                const __nv_bfloat16* xp = prm.x + ocol;
                xq[0] = __bfloat162float(xp[0]); xq[1] = __bfloat162float(xp[8]); xq[2] = __bfloat162float(xp[(lane & 3) < 2 ? 16 : 0]);
            }
            if (t == TWO && warp < 6) {
                mbar_wait(sb + BAR_WO + warp * 8, 0);
#pragma unroll
                for (int ks = 0; ks < 4; ks++)
#pragma unroll
                    for (int mt = 0; mt < 4; mt++) ldsm4t(wa[mt][ks], wo_addr[mt] + ks * 2048);
            }
            uint32_t pb[2][4];
            ldB(pb[0], sb + OFF_P, P_PITCH * 2, NA * 32 + (t - NA) * 256 + (warp >> 1) * 64, zero, lane);
            ldB(pb[1], sb + OFF_P, P_PITCH * 2, NA * 32 + (t - NA) * 256 + (warp >> 1) * 64 + 32, zero, lane);
            mbar_wait(sb + BAR_FULL + ((NT + t) % NS) * 8, ((NT + t) / NS) & 1);
            const uint32_t base = sb + OFF_RING + ((NT + t) % NS) * SLOT + voff2;
            uint32_t a[4][4];
            ldsm4t(a[0], base); ldsm4t(a[1], base + 1024); ldsm4t(a[2], base + 2048); ldsm4t(a[3], base + 3072);
            mma16816(o0, a[0], pb[0][0], pb[0][1]);
            mma16816(o1, a[1], pb[0][2], pb[0][3]);
            mma16816(o2, a[2], pb[1][0], pb[1][1]);
            mma16816(o3, a[3], pb[1][2], pb[1][3]);
        }
        sts128_if((lane & 3) == 0, part_st, (o0[0] + o1[0]) + (o2[0] + o3[0]), (o0[1] + o1[1]) + (o2[1] + o3[1]),
                  (o0[2] + o1[2]) + (o2[2] + o3[2]), (o0[3] + o1[3]) + (o2[3] + o3[3]));
    }
    if (warp == 7) { bar_arrive(2, 256); return; }
    bar_sync(2, 256);
    const float2 v0 = lds64(part_ld), v1 = lds64(part_ld + 256), v2 = lds64(part_ld + 512), v3 = lds64(part_ld + 768);
    const uint32_t ow = pack_bf16((v0.x + v1.x) + (v2.x + v3.x), (v0.y + v1.y) + (v2.y + v3.y));
    if (warp == 6) {
        mbar_wait(sb + BAR_WO + warp * 8, 0);
#pragma unroll
        for (int ks = 0; ks < 4; ks++)
#pragma unroll
            for (int mt = 0; mt < 4; mt++) ldsm4t(wa[mt][ks], wo_addr[mt] + ks * 2048);
    }
    float acc[2][4][4] = {};
#pragma unroll
    for (int ks = 0; ks < 4; ks++) {
        const uint32_t b0 = __shfl_sync(~0u, ow, ks * 8 + (lane & 3));
        const uint32_t b1 = __shfl_sync(~0u, ow, ks * 8 + 4 + (lane & 3));
#pragma unroll
        for (int mt = 0; mt < 4; mt++) mma16816(acc[ks & 1][mt], wa[mt][ks], b0, b1);
    }
    const int t4 = lane & 3;
    float sum[8];
#pragma unroll
    for (int mt = 0; mt < 4; mt++) { sum[2 * mt] = acc[0][mt][0] + acc[1][mt][0]; sum[2 * mt + 1] = acc[0][mt][2] + acc[1][mt][2]; }
    const float a0 = fsel(t4 == 0, sum[0], fsel(t4 == 1, sum[3], sum[6]));
    const float a1 = fsel(t4 == 0, sum[1], fsel(t4 == 1, sum[4], sum[7]));
    const float a2 = fsel(t4 == 0, sum[2], fsel(t4 == 1, sum[5], 0.f));
    if (t4 < 3) {
        float o0, o1, o2, cnt;
        asm volatile("atom.relaxed.gpu.global.add.v4.f32 {%0,%1,%2,%3}, [%4], {%5,%6,%7,%8};"
                     : "=f"(o0), "=f"(o1), "=f"(o2), "=f"(cnt) : "l"(acc_dst), "f"(a0), "f"(a1), "f"(a2), "f"(1.0f) : "memory");
        if (cnt == 63.f) {
            int it = 0;
            while ((pkt_diff(gv, tag) & 3u) && ++it < POLL_MAX) gv = pkt_load(g_src);
            const uint32_t r01 = pack_bf16(xq[0] + bf16r(bf16r(o0 + a0) * pkt_f(gv.x)), xq[1] + bf16r(bf16r(o1 + a1) * pkt_f(gv.y)));
            const uint32_t r2 = pack_bf16(xq[2] + bf16r(bf16r(o2 + a2) * pkt_f(gv.z)), 0.f);
            asm volatile("st.global.u16 [%0], %1;" :: "l"(out_dst), "h"((unsigned short)r01) : "memory");
            asm volatile("st.global.u16 [%0+16], %1;" :: "l"(out_dst), "h"((unsigned short)(r01 >> 16)) : "memory");
            if (t4 < 2) asm volatile("st.global.u16 [%0+32], %1;" :: "l"(out_dst), "h"((unsigned short)r2) : "memory");
        }
    }
}

typedef CUresult (*EncodeFn)(CUtensorMap*, CUtensorMapDataType, cuuint32_t, void*, const cuuint64_t*, const cuuint64_t*,
                             const cuuint32_t*, const cuuint32_t*, CUtensorMapInterleave, CUtensorMapSwizzle,
                             CUtensorMapL2promotion, CUtensorMapFloatOOBfill);

void make_map(EncodeFn enc, CUtensorMap* m, const void* ptr, uint64_t cols, uint64_t rows, uint32_t bc, uint32_t br,
              CUtensorMapSwizzle sw) {
    cuuint64_t dims[2] = {cols, rows};
    cuuint64_t strides[1] = {cols * 2};
    cuuint32_t box[2] = {bc, br};
    cuuint32_t es[2] = {1, 1};
    enc(m, CU_TENSOR_MAP_DATA_TYPE_BFLOAT16, 2, const_cast<void*>(ptr), dims, strides, box, es,
        CU_TENSOR_MAP_INTERLEAVE_NONE, sw, CU_TENSOR_MAP_L2_PROMOTION_L2_128B, CU_TENSOR_MAP_FLOAT_OOB_FILL_NONE);
}

}

extern "C" void kernel_launch(void* const* d_in, const int* in_sizes, int n_in, void* d_out, int out_size) {
    (void)in_sizes; (void)n_in; (void)out_size;
    static EncodeFn enc = nullptr;
    static Scratch* scratch = nullptr;
    if (!enc) {
        void* fn = nullptr;
        cudaDriverEntryPointQueryResult qr;
        cudaGetDriverEntryPoint("cuTensorMapEncodeTiled", &fn, cudaEnableDefault, &qr);
        enc = (EncodeFn)fn;
        cudaGetSymbolAddress((void**)&scratch, g_scratch);
        cudaFuncSetAttribute(fused_decode_kernel, cudaFuncAttributeMaxDynamicSharedMemorySize, SMEM_BYTES);
    }
    Params p;
    p.k = (const uint8_t*)d_in[1];
    p.wq_raw = (const uint8_t*)d_in[3];
    p.x = (const __nv_bfloat16*)d_in[0];
    p.out = (__nv_bfloat16*)d_out;
    p.sx = scratch;
    make_map(enc, &p.v,  d_in[2], 256,  (uint64_t)16 * SK, 32, 256, CU_TENSOR_MAP_SWIZZLE_64B);
    {
        cuuint64_t dims[3] = {64, (cuuint64_t)16 * SK, 4};
        cuuint64_t strides[2] = {512, 128};
        cuuint32_t box[3] = {64, 32, 4};
        cuuint32_t es[3] = {1, 1, 1};
        enc(&p.va, CU_TENSOR_MAP_DATA_TYPE_BFLOAT16, 3, d_in[2], dims, strides, box, es, CU_TENSOR_MAP_INTERLEAVE_NONE,
            CU_TENSOR_MAP_SWIZZLE_128B, CU_TENSOR_MAP_L2_PROMOTION_NONE, CU_TENSOR_MAP_FLOAT_OOB_FILL_NONE);
    }
    make_map(enc, &p.wq, d_in[3], 4096, D,  64, 224, CU_TENSOR_MAP_SWIZZLE_128B);
    {
        cuuint64_t dims[5] = {D, 16, 2, 8, 16};
        cuuint64_t strides[4] = {256 * D * 2, 8 * D * 2, D * 2, 16 * D * 2};
        cuuint32_t box[5] = {64, 2, 2, 8, 2};
        cuuint32_t es[5] = {1, 1, 1, 1, 1};
        enc(&p.wo, CU_TENSOR_MAP_DATA_TYPE_BFLOAT16, 5, d_in[4], dims, strides, box, es, CU_TENSOR_MAP_INTERLEAVE_NONE,
            CU_TENSOR_MAP_SWIZZLE_128B, CU_TENSOR_MAP_L2_PROMOTION_L2_128B, CU_TENSOR_MAP_FLOAT_OOB_FILL_NONE);
    }
    make_map(enc, &p.wg, d_in[6], FF,   D,  64, 224, CU_TENSOR_MAP_SWIZZLE_128B);
    make_map(enc, &p.wu, d_in[7], FF,   D,  64, 224, CU_TENSOR_MAP_SWIZZLE_128B);
    make_map(enc, &p.wd, d_in[8], D,    FF, 64, 128, CU_TENSOR_MAP_SWIZZLE_128B);
    fused_decode_kernel<<<NCTA, NTHREADS, SMEM_BYTES, cudaStreamPerThread>>>(p);
}
```

```cpp
#include <cuda_runtime.h>
#include <cuda_bf16.h>
#include <cuda.h>
#include <stdint.h>

namespace {

constexpr int D = 448, SK = 32768, WIN = 4096, FF = 1792;
constexpr int NMAIN = 128, NHELP = 4, NCTA = NMAIN + NHELP;
constexpr int NS = 9;
constexpr int SLOT = 16384;
constexpr int NT = 16;
constexpr int NTHREADS = 288;

constexpr int MB = 4, NA = NT - MB;
constexpr int KDEPTH = 3;
constexpr int VDEPTH = 2;
constexpr int NSTART = 2;
constexpr int GUPOS = 5;
constexpr int GUT = 6;
constexpr int WOPOS = 20;
constexpr int TSC = 8, TSTAT = 10;
constexpr int TWO = 13;
constexpr int TO = 14;

constexpr int OFF_RING = 0;
constexpr int OFF_W    = OFF_RING + NS * SLOT;
constexpr int OFF_P    = OFF_W + 57344;
constexpr int P_PITCH  = NA * 32 + MB * 256 + 8;
constexpr int OFF_SC   = OFF_P + 2 * P_PITCH * 2;
constexpr int OFF_XN   = OFF_SC + NA * 256;
constexpr int XN_PITCH = 456;
constexpr int OFF_Q    = OFF_XN + 2 * XN_PITCH * 2;
constexpr int OFF_ZERO = OFF_Q + 1024;
constexpr int OFF_PART = OFF_ZERO + 16;
constexpr int OFF_PART2 = OFF_PART + 2048;
constexpr int OFF_RED  = OFF_PART2 + 1024;
constexpr int OFF_TAG  = OFF_RED + 128;
constexpr int OFF_BAR  = OFF_TAG + 16;
constexpr int BAR_FULL = OFF_BAR, BAR_EMPTY = BAR_FULL + NS * 8;
constexpr int BAR_WQ = BAR_EMPTY + NS * 8, BAR_GU = BAR_WQ + 8, BAR_WO = BAR_GU + 8, BAR_WFREE = BAR_WO + 7 * 8;
constexpr int SMEM_BYTES = BAR_WFREE + 8 + 1024;
constexpr int H_PITCH = FF + 8;
static_assert(OFF_XN % 16 == 0 && OFF_Q % 16 == 0 && OFF_P % 16 == 0 && OFF_PART % 16 == 0 && OFF_BAR % 8 == 0, "align");
static_assert(SMEM_BYTES <= 232448, "smem");

struct __align__(4096) Scratch {
    float4 acc[2][2][256];
    uint4 sc[16 * MB * 128];
    uint4 o[NMAIN * 8 * 16];
    uint4 ml[NMAIN];
    uint4 q[NMAIN * 32];
    uint4 h[112 * 32];
    uint4 g[2 * 7 * 32];
    unsigned epoch[NCTA];
};
__device__ Scratch g_scratch;

struct Params {
    const uint8_t* wq_raw;
    const uint8_t* k;
    const __nv_bfloat16* x;
    __nv_bfloat16* out;
    Scratch* sx;
    alignas(64) CUtensorMap wq;
    CUtensorMap v, va, wg, wu, wo, wd;
};


__device__ __forceinline__ uint32_t smem_u32(const void* p) { return (uint32_t)__cvta_generic_to_shared(p); }
__device__ __forceinline__ bool elect_one() {
    uint32_t p;
    asm volatile("{\n.reg .pred P;\nelect.sync _|P, 0xffffffff;\nselp.u32 %0, 1, 0, P;\n}" : "=r"(p));
    return p;
}
__device__ __forceinline__ void mbar_init(uint32_t bar, uint32_t cnt) {
    asm volatile("mbarrier.init.shared::cta.b64 [%0], %1;" :: "r"(bar), "r"(cnt) : "memory");
}
__device__ __forceinline__ void mbar_expect_tx(uint32_t bar, uint32_t bytes) {
    asm volatile("mbarrier.arrive.expect_tx.shared::cta.b64 _, [%0], %1;" :: "r"(bar), "r"(bytes) : "memory");
}
__device__ __forceinline__ void mbar_arrive(uint32_t bar, uint32_t cnt) {
    asm volatile("mbarrier.arrive.shared::cta.b64 _, [%0], %1;" :: "r"(bar), "r"(cnt) : "memory");
}
__device__ __forceinline__ void mbar_wait(uint32_t bar, uint32_t parity) {
    uint32_t ok;
    int it = 0;
    do {
        asm volatile("{\n.reg .pred p;\nmbarrier.test_wait.parity.shared::cta.b64 p, [%1], %2;\nselp.u32 %0, 1, 0, p;\n}"
                     : "=r"(ok) : "r"(bar), "r"(parity) : "memory");
    } while (!ok && ++it < (1 << 24));
}
__device__ __forceinline__ void bulk1d(uint32_t dst, const void* src, uint32_t bytes, uint32_t bar, uint64_t pol) {
    asm volatile("cp.async.bulk.shared::cluster.global.mbarrier::complete_tx::bytes.L2::cache_hint [%0], [%1], %2, [%3], %4;"
                 :: "r"(dst), "l"(src), "r"(bytes), "r"(bar), "l"(pol) : "memory");
}
__device__ __forceinline__ void tma2d(uint32_t dst, const CUtensorMap* map, int c0, int c1, uint32_t bar, uint64_t pol) {
    asm volatile("cp.async.bulk.tensor.2d.shared::cluster.global.mbarrier::complete_tx::bytes.L2::cache_hint [%0], [%1, {%3, %4}], [%2], %5;"
                 :: "r"(dst), "l"(map), "r"(bar), "r"(c0), "r"(c1), "l"(pol) : "memory");
}
__device__ __forceinline__ void tma3d(uint32_t dst, const CUtensorMap* map, int c1, uint32_t bar, uint64_t pol) {
    asm volatile("cp.async.bulk.tensor.3d.shared::cluster.global.mbarrier::complete_tx::bytes.L2::cache_hint [%0], [%1, {%4, %3, %4}], [%2], %5;"
                 :: "r"(dst), "l"(map), "r"(bar), "r"(c1), "r"(0), "l"(pol) : "memory");
}
__device__ __forceinline__ void tma5d(uint32_t dst, const CUtensorMap* map, int c0, int c1, int c4, uint32_t bar, uint64_t pol) {
    asm volatile("cp.async.bulk.tensor.5d.shared::cluster.global.mbarrier::complete_tx::bytes.L2::cache_hint [%0], [%1, {%3, %4, %6, %6, %5}], [%2], %7;"
                 :: "r"(dst), "l"(map), "r"(bar), "r"(c0), "r"(c1), "r"(c4), "r"(0), "l"(pol) : "memory");
}
__device__ __forceinline__ void ldsm4(uint32_t (&r)[4], uint32_t addr) {
    asm volatile("ldmatrix.sync.aligned.m8n8.x4.shared.b16 {%0,%1,%2,%3}, [%4];"
                 : "=r"(r[0]), "=r"(r[1]), "=r"(r[2]), "=r"(r[3]) : "r"(addr) : "memory");
}
__device__ __forceinline__ void ldsm4t(uint32_t (&r)[4], uint32_t addr) {
    asm volatile("ldmatrix.sync.aligned.m8n8.x4.trans.shared.b16 {%0,%1,%2,%3}, [%4];"
                 : "=r"(r[0]), "=r"(r[1]), "=r"(r[2]), "=r"(r[3]) : "r"(addr) : "memory");
}
__device__ __forceinline__ void lds128(uint32_t (&r)[4], uint32_t addr) {
    asm volatile("ld.shared.v4.u32 {%0,%1,%2,%3}, [%4];"
                 : "=r"(r[0]), "=r"(r[1]), "=r"(r[2]), "=r"(r[3]) : "r"(addr) : "memory");
}
__device__ __forceinline__ void sts128_if(bool c, uint32_t addr, float x, float y, float z, float w) {
    asm volatile("{\n.reg .pred p;\nsetp.ne.u32 p, %5, 0;\n@p st.shared.v4.f32 [%0], {%1,%2,%3,%4};\n}"
                 :: "r"(addr), "f"(x), "f"(y), "f"(z), "f"(w), "r"((uint32_t)c) : "memory");
}
__device__ __forceinline__ float2 lds64(uint32_t addr) {
    float2 v;
    asm volatile("ld.shared.v2.f32 {%0,%1}, [%2];" : "=f"(v.x), "=f"(v.y) : "r"(addr) : "memory");
    return v;
}
#define PIN32(x) asm volatile("" : "+r"(x))
#define PIN64(x) asm volatile("" : "+l"(x))
__device__ __forceinline__ void mma16816(float (&c)[4], uint32_t a0, uint32_t a1, uint32_t a2, uint32_t a3, uint32_t b0, uint32_t b1) {
    asm volatile("mma.sync.aligned.m16n8k16.row.col.f32.bf16.bf16.f32 {%0,%1,%2,%3}, {%4,%5,%6,%7}, {%8,%9}, {%0,%1,%2,%3};"
                 : "+f"(c[0]), "+f"(c[1]), "+f"(c[2]), "+f"(c[3])
                 : "r"(a0), "r"(a1), "r"(a2), "r"(a3), "r"(b0), "r"(b1));
}
__device__ __forceinline__ void mma16816(float (&c)[4], const uint32_t (&a)[4], uint32_t b0, uint32_t b1) {
    mma16816(c, a[0], a[1], a[2], a[3], b0, b1);
}
__device__ __forceinline__ void bar_sync(int id, int n) { asm volatile("bar.sync %0, %1;" :: "r"(id), "r"(n) : "memory"); }
__device__ __forceinline__ void bar_arrive(int id, int n) { asm volatile("bar.arrive %0, %1;" :: "r"(id), "r"(n) : "memory"); }
__device__ __forceinline__ uint32_t pack_bf16(float lo, float hi) {
    uint32_t r;
    asm("cvt.rn.bf16x2.f32 %0, %1, %2;" : "=r"(r) : "f"(hi), "f"(lo));
    return r;
}
__device__ __forceinline__ float bf16r(float v) { return __uint_as_float(pack_bf16(0.f, v)); }

__device__ __forceinline__ float fsel(bool c, float a, float b) {
    float r;
    asm("{\n.reg .pred p;\nsetp.ne.u32 p, %3, 0;\nselp.f32 %0, %1, %2, p;\n}" : "=f"(r) : "f"(a), "f"(b), "r"((uint32_t)c));
    return r;
}

__device__ __forceinline__ __nv_bfloat16 geglu(float gate, float up) {
    const float ga = bf16r(gate);
    const float in = 0.7978845608028654f * (ga + 0.044715f * ga * ga * ga);
    return __float2bfloat16_rn(bf16r(0.5f * ga * (1.0f + tanhf(in))) * bf16r(up));
}

__device__ __forceinline__ void ldB(uint32_t (&r)[4], uint32_t base, int pitch_bytes, int k0, uint32_t zero, int lane) {
    const int n = lane & 7;
    ldsm4(r, n < 2 ? base + n * pitch_bytes + (k0 + 8 * (lane >> 3)) * 2 : zero);
}

__device__ __forceinline__ void pkt_store(uint4* p, float a, float b, float c, float d, uint32_t tag) {
    const uint32_t w0 = (__float_as_uint(a) & ~3u) | (tag & 3u);
    const uint32_t w1 = (__float_as_uint(b) & ~3u) | ((tag >> 2) & 3u);
    const uint32_t w2 = (__float_as_uint(c) & ~3u) | ((tag >> 4) & 3u);
    const uint32_t w3 = (__float_as_uint(d) & ~3u) | ((tag >> 6) & 3u);
    asm volatile("{\n.reg .b128 t;\n.reg .b64 lo, hi;\nmov.b64 lo, {%1, %2};\nmov.b64 hi, {%3, %4};\nmov.b128 t, {lo, hi};\n"
                 "st.relaxed.gpu.global.b128 [%0], t;\n}"
                 :: "l"(p), "r"(w0), "r"(w1), "r"(w2), "r"(w3) : "memory");
}
__device__ __forceinline__ void pkt_clear(uint4* p) { pkt_store(p, 0.f, 0.f, 0.f, 0.f, 0); }
__device__ __forceinline__ uint4 pkt_load(const uint4* p) {
    uint4 v;
    asm volatile("{\n.reg .b128 t;\n.reg .b64 lo, hi;\nld.relaxed.gpu.global.b128 t, [%4];\nmov.b128 {lo, hi}, t;\n"
                 "mov.b64 {%0, %1}, lo;\nmov.b64 {%2, %3}, hi;\n}"
                 : "=r"(v.x), "=r"(v.y), "=r"(v.z), "=r"(v.w) : "l"(p) : "memory");
    return v;
}
__device__ __forceinline__ uint32_t pkt_diff(const uint4& v, uint32_t tag) {
    return ((v.x ^ tag) | (v.y ^ (tag >> 2))) | ((v.z ^ (tag >> 4)) | (v.w ^ (tag >> 6)));
}
__device__ __forceinline__ float pkt_f(uint32_t w) { return __uint_as_float(w & ~3u); }
constexpr int POLL_MAX = 1 << 20;

__global__ void __launch_bounds__(NTHREADS, 1) fused_decode_kernel(const __grid_constant__ Params prm) {
    extern __shared__ uint8_t smem_raw[];
    const int cta = blockIdx.x;
    const int tid = threadIdx.x, lane = tid & 31;
    const bool is_main = cta < NMAIN;
    if (tid == 0 && is_main) {
        uint64_t pol;
        asm volatile("createpolicy.fractional.L2::evict_normal.b64 %0, 1.0;" : "=l"(pol));
        asm volatile("cp.async.bulk.prefetch.L2.global.L2::cache_hint [%0], %1, %2;"
                     :: "l"(prm.wq_raw + cta * 28672), "r"(28672), "l"(pol) : "memory");
    }
    const int warp = __shfl_sync(~0u, tid >> 5, 0);

    const uint32_t sb = (smem_u32(smem_raw) + 1023u) & ~1023u;
    const int grp = cta >> 3, j = cta & 7;
    const int b = grp >> 3;
    const bool has_ffn = is_main && j < 7;
    const int fblk = grp * 7 + j;
    const int qblk = (grp & 7) * 16 + b * 8 + j;
    const int ncg = is_main ? 0 : (cta - NMAIN < 3 ? 2 : 1);
    const int cg0 = (cta - NMAIN) * 2;
    Scratch* const sx = prm.sx;
    uint8_t* const sm = smem_raw + (sb - smem_u32(smem_raw));
    volatile uint32_t* const s_tag = reinterpret_cast<volatile uint32_t*>(sm + OFF_TAG);

    if (warp == 8 && elect_one()) {
        uint64_t pol, npol;
        asm volatile("createpolicy.fractional.L2::evict_first.b64 %0, 1.0;" : "=l"(pol));
        asm volatile("createpolicy.fractional.L2::evict_normal.b64 %0, 1.0;" : "=l"(npol));
        const uint8_t* const ksrc = prm.k + (uint32_t)((grp * SK + (SK - WIN) + j * 32) * 512);
#pragma unroll
        for (int i = 0; i < NSTART; i++) mbar_init(sb + BAR_FULL + i * 8, 1);
        mbar_init(sb + BAR_WQ, 1);
        asm volatile("fence.mbarrier_init.release.cluster;" ::: "memory");
        if (is_main) {
            mbar_expect_tx(sb + BAR_WQ, 28672);
            tma2d(sb + OFF_W, &prm.wq, (qblk >> 1) * 64, (qblk & 1) * 224, sb + BAR_WQ, npol);
#pragma unroll
            for (int i = 0; i < NSTART; i++) {
                mbar_expect_tx(sb + BAR_FULL + i * 8, SLOT);
                bulk1d(sb + OFF_RING + i * SLOT, ksrc + (size_t)i * 256 * 512, SLOT, sb + BAR_FULL + i * 8, pol);
            }
        }
#pragma unroll
        for (int i = NSTART; i < NS; i++) mbar_init(sb + BAR_FULL + i * 8, 1);
#pragma unroll
        for (int i = 0; i < NS; i++) mbar_init(sb + BAR_EMPTY + i * 8, 8);
        mbar_init(sb + BAR_GU, 1); mbar_init(sb + BAR_WFREE, 8);
#pragma unroll
        for (int c = 0; c < 7; c++) mbar_init(sb + BAR_WO + c * 8, 1);
        asm volatile("fence.mbarrier_init.release.cluster;" ::: "memory");
    }

    const uint32_t zero = sb + OFF_ZERO;
    float* const s_part = reinterpret_cast<float*>(sm + OFF_PART);
    float* const s_red = reinterpret_cast<float*>(sm + OFF_RED);
    uint32_t xw[7];
    if (warp < 2 && is_main) {
        const uint32_t* xp = reinterpret_cast<const uint32_t*>(prm.x + warp * D);
#pragma unroll
        for (int i = 0; i < 7; i++) xw[i] = __ldg(xp + lane + 32 * i);
    }
    unsigned epoch = 0;
    if (tid == 64) epoch = sx->epoch[cta];
    if (tid == 96) *reinterpret_cast<uint4*>(sm + OFF_ZERO) = make_uint4(0, 0, 0, 0);
    if (is_main) {
        if (warp == 4) pkt_clear(&sx->q[qblk * 32 + lane]);
        if (warp == 5 && has_ffn) pkt_clear(&sx->h[fblk * 32 + lane]);
    } else if (warp < ncg * 2) {
        pkt_clear(&sx->g[((warp & 1) * 7 + cg0 + (warp >> 1)) * 32 + lane]);
    }
    __syncthreads();

    if (warp == 8) {
        const bool leader = elect_one();
        int ucta;
        asm volatile("mov.u32 %0, %%ctaid.x;" : "=r"(ucta));
        const uint8_t* const ksrc = prm.k + (uint32_t)(((ucta >> 3) * SK + (SK - WIN) + (ucta & 7) * 32) * 512);
        uint64_t pol, npol;
        asm volatile("createpolicy.fractional.L2::evict_first.b64 %0, 1.0;" : "=l"(pol));
        asm volatile("createpolicy.fractional.L2::evict_normal.b64 %0, 1.0;" : "=l"(npol));
        if (is_main) {
            if (leader) {
                asm volatile("prefetch.tensormap [%0];" :: "l"((fblk & 1) ? &prm.wu : &prm.wg) : "memory");
                asm volatile("prefetch.tensormap [%0];" :: "l"(&prm.va) : "memory");
                asm volatile("prefetch.tensormap [%0];" :: "l"(&prm.v) : "memory");
                asm volatile("prefetch.tensormap [%0];" :: "l"(&prm.wo) : "memory");
            }
            const int vrow = (ucta >> 3) * SK + (SK - WIN), vcol = (ucta & 7) * 32, wohead = ((ucta >> 3) & 7) * 2, woblk = (ucta & 7) * 2;
            uint32_t so = NSTART * 8, eph = 1, lo = 0, lph = 0;
            auto acquire = [&](int n) {
                if (n >= NS) mbar_wait(sb + BAR_EMPTY + so, eph);
                if (leader) mbar_expect_tx(sb + BAR_FULL + so, SLOT);
            };
            auto landing = [&]() {
                mbar_wait(sb + BAR_FULL + lo, lph);
            };
            auto advance = [&](bool l) {
                so += 8; if (so == NS * 8) { so = 0; eph ^= 1; }
                if (l) { lo += 8; if (lo == NS * 8) { lo = 0; lph ^= 1; } }
            };
            acquire(NSTART);
            mbar_wait(sb + BAR_WQ, 0);
            if (leader) bulk1d(sb + OFF_RING + so * (SLOT / 8), ksrc + NSTART * 256 * 512, SLOT, sb + BAR_FULL + so, pol);
            advance(false);
            const uint8_t* src = ksrc + (NSTART + 1) * 256 * 512;
#pragma unroll 1
            for (int n = NSTART + 1; n < NT; n++) {
                acquire(n);
                const uint32_t bar = sb + BAR_FULL + so, dst = sb + OFF_RING + so * (SLOT / 8);
                landing();
                if (leader) bulk1d(dst, src, SLOT, bar, pol);
                if (n == GUPOS && has_ffn && leader) {
                    mbar_expect_tx(sb + BAR_GU, 28672);
                    tma2d(sb + OFF_W + 28672, (fblk & 1) ? &prm.wu : &prm.wg, (fblk >> 2) * 64, ((fblk >> 1) & 1) * 224, sb + BAR_GU, npol);
                }
                src += 256 * 512;
                advance(true);
            }
            int row = vrow + vcol;
#pragma unroll 1
            for (int n = NT; n < NT + NA; n++) {
                acquire(n);
                if (n == WOPOS) mbar_wait(sb + BAR_WFREE, 0);
                const uint32_t bar = sb + BAR_FULL + so, dst = sb + OFF_RING + so * (SLOT / 8);
                landing();
                if (leader) tma3d(dst, &prm.va, row, bar, pol);
                if (n >= WOPOS && n < WOPOS + 6 && leader) {
                    const int c = n - WOPOS;
                    mbar_expect_tx(sb + BAR_WO + c * 8, 8192);
                    tma5d(sb + OFF_W + c * 8192, &prm.wo, c * 64, wohead, woblk, sb + BAR_WO + c * 8, npol);
                }
                row += 256;
                advance(true);
            }
            static_assert(KDEPTH == NSTART + 1 && VDEPTH == KDEPTH - 1 && WOPOS >= NT && WOPOS + 7 <= NT + NA, "producer loops");
            row = vrow + NA * 256;
            landing();
            lo += 8; if (lo == NS * 8) { lo = 0; lph ^= 1; }
#pragma unroll 1
            for (int n = NT + NA; n < 2 * NT; n++) {
                acquire(n);
                const uint32_t bar = sb + BAR_FULL + so, dst = sb + OFF_RING + so * (SLOT / 8);
                landing();
                if (leader) tma2d(dst, &prm.v, vcol, row, bar, pol);
                row += 256;
                advance(true);
            }
            if (leader) mbar_expect_tx(sb + BAR_WO + 6 * 8, 8192);
            landing();
            if (leader) tma5d(sb + OFF_W + 6 * 8192, &prm.wo, 6 * 64, wohead, woblk, sb + BAR_WO + 6 * 8, npol);
            if (cta < 12) sx->acc[(s_tag[1] + 1) & 1][cta / 6][(cta % 6) * 32 + lane] = make_float4(0.f, 0.f, 0.f, 0.f);
        } else {
            int slot = 0, ph = 1;
            for (int n = 0; n < 14 * ncg; n++) {
                if (n >= NS) mbar_wait(sb + BAR_EMPTY + slot * 8, ph);
                if (leader) {
                    mbar_expect_tx(sb + BAR_FULL + slot * 8, SLOT);
                    tma2d(sb + OFF_RING + slot * SLOT, &prm.wd, (cg0 + (ncg == 2 ? (n & 1) : 0)) * 64, (ncg == 2 ? (n >> 1) : n) * 128,
                          sb + BAR_FULL + slot * 8, npol);
                }
                if (++slot == NS) { slot = 0; ph ^= 1; }
            }
        }
        return;
    }


    if (!is_main) {
        if (tid == 64) { sx->epoch[cta] = epoch + 1; s_tag[0] = epoch % 255u + 1u; }
        bar_sync(1, 256);
        const uint32_t tag = s_tag[0];
        __nv_bfloat16* h_s = reinterpret_cast<__nv_bfloat16*>(sm + OFF_W);
        {
            uint4 v[4][4];
            const int ncb = warp < 4 ? 4 : 3;
            int it = 0;
            uint32_t bad;
            do {
                if (it) __nanosleep(200);
                bad = 0;
#pragma unroll
                for (int i = 0; i < 4; i++)
#pragma unroll
                    for (int q = 0; q < 4; q++)
                        if (i < ncb) v[i][q] = pkt_load(&sx->h[(warp + 8 * i) * 128 + q * 32 + lane]);
#pragma unroll
                for (int i = 0; i < 4; i++)
                    if (i < ncb) bad |= (pkt_diff(v[i][0], tag) | pkt_diff(v[i][1], tag)) | (pkt_diff(v[i][2], tag) | pkt_diff(v[i][3], tag));
            } while ((bad & 3u) && ++it < POLL_MAX);
#pragma unroll
            for (int i = 0; i < 4; i++) {
                if (i < ncb) {
                    __nv_bfloat16* dst = h_s + (warp + 8 * i) * 64 + (lane >> 3) * 16 + (lane & 7);
                    dst[0]           = geglu(pkt_f(v[i][0].x) + pkt_f(v[i][2].x), pkt_f(v[i][1].x) + pkt_f(v[i][3].x));
                    dst[H_PITCH]     = geglu(pkt_f(v[i][0].y) + pkt_f(v[i][2].y), pkt_f(v[i][1].y) + pkt_f(v[i][3].y));
                    dst[8]           = geglu(pkt_f(v[i][0].z) + pkt_f(v[i][2].z), pkt_f(v[i][1].z) + pkt_f(v[i][3].z));
                    dst[H_PITCH + 8] = geglu(pkt_f(v[i][0].w) + pkt_f(v[i][2].w), pkt_f(v[i][1].w) + pkt_f(v[i][3].w));
                }
            }
        }
        bar_sync(1, 256);
        const int mt = warp & 3, kh = warp >> 2;
        float acc[2][4] = {};
        int slot = 0, ph = 0;
        for (int rb = 0; rb < 14; rb++) {
            uint32_t bf[2][4];
            ldB(bf[0], sb + OFF_W, H_PITCH * 2, rb * 128 + kh * 64, zero, lane);
            ldB(bf[1], sb + OFF_W, H_PITCH * 2, rb * 128 + kh * 64 + 32, zero, lane);
#pragma unroll
            for (int ci = 0; ci < 2; ci++) {
                if (ci < ncg) {
                    mbar_wait(sb + BAR_FULL + slot * 8, ph);
                    const uint32_t base = sb + OFF_RING + slot * SLOT;
#pragma unroll
                    for (int ks = 0; ks < 4; ks++) {
                        const int row = kh * 64 + ks * 16 + (lane & 7) + 8 * (lane >> 4);
                        const int ch = 2 * mt + ((lane >> 3) & 1);
                        uint32_t a[4];
                        ldsm4t(a, base + row * 128 + ((ch ^ (row & 7)) << 4));
                        mma16816(acc[ci], a, bf[ks >> 1][(ks & 1) * 2], bf[ks >> 1][(ks & 1) * 2 + 1]);
                    }
                    __syncwarp();
                    if (lane == 0) mbar_arrive(sb + BAR_EMPTY + slot * 8, 1);
                    if (++slot == NS) { slot = 0; ph ^= 1; }
                }
            }
        }
        if ((lane & 3) == 0) {
#pragma unroll
            for (int ci = 0; ci < 2; ci++) {
                float* p = s_part + kh * 256 + ci * 128 + (mt * 16 + (lane >> 2)) * 2;
                p[0] = acc[ci][0]; p[1] = acc[ci][1]; p[16] = acc[ci][2]; p[17] = acc[ci][3];
            }
        }
        bar_sync(1, 256);
        if (warp < ncg * 2) {
            const int ci = warp >> 1, bb = warp & 1;
            float g[3];
#pragma unroll
            for (int i = 0; i < 3; i++) {
                const int col = ((lane >> 2) + 8 * (3 * (lane & 3) + i)) & 63;
                const float y = bf16r(s_part[ci * 128 + col * 2 + bb] + s_part[256 + ci * 128 + col * 2 + bb]);
                g[i] = bf16r(y / (1.0f + expf(-y)));
            }
            pkt_store(&sx->g[(bb * 7 + cg0 + ci) * 32 + lane], g[0], g[1], g[2], 0.f, tag);
        }
        return;
    }

    if (warp < 2) {
        float xv[14], sum = 0.f;
#pragma unroll
        for (int i = 0; i < 7; i++) {
            xv[2 * i] = __uint_as_float(xw[i] << 16);
            xv[2 * i + 1] = __uint_as_float(xw[i] & 0xffff0000u);
            sum += xv[2 * i] + xv[2 * i + 1];
        }
#pragma unroll
        for (int o = 16; o; o >>= 1) sum += __shfl_xor_sync(~0u, sum, o);
        const float mean = sum * (1.0f / D);
        float var = 0.f;
#pragma unroll
        for (int i = 0; i < 14; i++) { const float d = xv[i] - mean; var += d * d; }
#pragma unroll
        for (int o = 16; o; o >>= 1) var += __shfl_xor_sync(~0u, var, o);
        const float mb = bf16r(mean);
        const float sd = bf16r(sqrtf(bf16r(bf16r(var * (1.0f / D)) + 1e-5f)));
        uint32_t* xn = reinterpret_cast<uint32_t*>(sm + OFF_XN + warp * XN_PITCH * 2);
#pragma unroll
        for (int i = 0; i < 7; i++) xn[lane + 32 * i] = pack_bf16(bf16r(xv[2 * i] - mb) / sd, bf16r(xv[2 * i + 1] - mb) / sd);
    }
    if (tid == 64) { sx->epoch[cta] = epoch + 1; s_tag[0] = epoch % 255u + 1u; s_tag[1] = epoch; }
    bar_sync(1, 256);
    const uint32_t tag = s_tag[0];
    float4* const acc_dst = &sx->acc[s_tag[1] & 1][b][warp * 24 + (lane >> 2) * 3 + (lane & 3)];

    auto project = [&](uint32_t wbase, int khalf, uint32_t bar, uint4* dst) {
        uint32_t xb[7][4];
#pragma unroll
        for (int i = 0; i < 7; i++) ldB(xb[i], sb + OFF_XN, XN_PITCH * 2, khalf * 224 + i * 32, zero, lane);
        float acc[2][4] = {};
        mbar_wait(bar, 0);
#pragma unroll
        for (int ks = 0; ks < 14; ks++) {
            const int row = ks * 16 + (lane & 7) + 8 * (lane >> 4);
            const int ch = 2 * (warp & 3) + ((lane >> 3) & 1);
            uint32_t a[4];
            ldsm4t(a, wbase + row * 128 + ((ch ^ (row & 7)) << 4));
            mma16816(acc[ks & 1], a, xb[ks >> 1][(ks & 1) * 2], xb[ks >> 1][(ks & 1) * 2 + 1]);
        }
        if ((lane & 3) == 0)
            pkt_store(dst + (warp & 3) * 8 + (lane >> 2), acc[0][0] + acc[1][0], acc[0][1] + acc[1][1], acc[0][2] + acc[1][2], acc[0][3] + acc[1][3], tag);
        __syncwarp();
        if (lane == 0) mbar_arrive(sb + BAR_WFREE, 1);
    };
    if (warp < 4) {
        project(sb + OFF_W, qblk & 1, sb + BAR_WQ, &sx->q[qblk * 32]);
    } else {
        if (!has_ffn && lane == 0) mbar_arrive(sb + BAR_WFREE, 1);
    }
    mbar_wait(sb + BAR_FULL + 2 * 8, 0);
    {
        const uint4* src = &sx->q[((grp & 7) * 8 + warp) * 64 + lane];
        uint4 u, v;
        int it = 0;
        do { u = pkt_load(src); v = pkt_load(src + 32); } while (((pkt_diff(u, tag) | pkt_diff(v, tag)) & 3u) && ++it < POLL_MAX);
        __nv_bfloat16* dst = reinterpret_cast<__nv_bfloat16*>(sm + OFF_Q) + warp * 64 + (lane >> 3) * 16 + (lane & 7);
        dst[0] = __float2bfloat16_rn(pkt_f(b ? u.y : u.x) + pkt_f(b ? v.y : v.x));
        dst[8] = __float2bfloat16_rn(pkt_f(b ? u.w : u.z) + pkt_f(b ? v.w : v.z));
    }
    bar_sync(1, 256);

    {
        const int g = lane >> 2, t4 = lane & 3;
        uint32_t qb[8][4];
#pragma unroll
        for (int i = 0; i < 8; i++) lds128(qb[i], sb + OFF_Q + (g & 1) * 512 + ((i ^ ((g >> 1) & 1)) * 32 + t4 * 8) * 2);
        const int mt = warp & 1;
        const uint32_t roff = (mt * 16 + 2 * g) * 512 + t4 * 16;
        for (int t = 0; t < NT; t++) {
            const int slot = t % NS;
            if ((slot & 3) != (warp >> 1)) continue;
            if (t >= GUT && t < GUT + 4 && warp >= 4 && has_ffn) project(sb + OFF_W + 28672, (fblk >> 1) & 1, sb + BAR_GU, &sx->h[fblk * 32]);
            mbar_wait(sb + BAR_FULL + slot * 8, (t / NS) & 1);
            const uint32_t base = sb + OFF_RING + slot * SLOT + roff;
            float acc0[4] = {}, acc1[4] = {};
#pragma unroll
            for (int i = 0; i < 8; i++) {
                uint32_t r0[4], r1[4];
                const uint32_t a = base + ((i ^ (g & 1)) << 6);
                lds128(r0, a);
                lds128(r1, a + 512);
                mma16816(acc0, r0[0], r1[0], r0[1], r1[1], qb[i][0], qb[i][1]);
                mma16816(acc1, r0[2], r1[2], r0[3], r1[3], qb[i][2], qb[i][3]);
            }
            __syncwarp();
            if (lane == 0) mbar_arrive(sb + BAR_EMPTY + slot * 8, 4);
            const float s0 = bf16r(acc0[0] + acc1[0]) * 0.0625f, s1 = bf16r(acc0[2] + acc1[2]) * 0.0625f;
            const float s2 = bf16r(acc0[1] + acc1[1]) * 0.0625f, s3 = bf16r(acc0[3] + acc1[3]) * 0.0625f;
            if (t < NA) sts128_if(t4 == (g & 1), sb + OFF_SC + ((t * 2 + mt) * 8 + g) * 16, s0, s1, s2, s3);
            else if (t4 == (g & 1)) pkt_store(&sx->sc[grp * MB * 128 + (((t - NA) * 8 + j) * 2 + mt) * 8 + g], s0, s1, s2, s3, tag);
        }
    }

    static_assert(VDEPTH <= KDEPTH && MB % 2 == 0 && TSC < TSTAT && TSTAT < NA && TWO >= NA && TO >= NA && NS > MB, "pipeline shape");
    const int ocol = b * D + warp * 64 + (lane >> 2) + 24 * ((lane & 3) < 3 ? (lane & 3) : 0);
    const uint4* g_src = &sx->g[(b * 7 + warp) * 32 + lane];
    const uint4* o_src = &sx->o[(cta * 8 + (warp & 6)) * 16 + (warp & 1) * 8 + (lane >> 2)];
    float xq[3] = {};
    if (warp < 7) {
        const __nv_bfloat16* xp = prm.x + ocol;
        xq[0] = __bfloat162float(xp[0]); xq[1] = __bfloat162float(xp[8]); xq[2] = __bfloat162float(xp[(lane & 3) < 2 ? 16 : 0]);
    }
    unsigned short* out_dst = reinterpret_cast<unsigned short*>(prm.out + ocol);
    uint32_t part_st = sb + OFF_PART2 + ((warp >> 1) * 64 + (warp & 1) * 32 + lane) * 4, part_ld = sb + OFF_PART2 + lane * 8;
    uint32_t wo_addr[4];
#pragma unroll
    for (int mt = 0; mt < 4; mt++) {
        const int row = (lane & 7) + 8 * (lane >> 4);
        wo_addr[mt] = sb + OFF_W + warp * 8192 + row * 128 + (((2 * mt + ((lane >> 3) & 1)) ^ (row & 7)) << 4);
        PIN32(wo_addr[mt]);
    }
    PIN64(out_dst); PIN64(g_src); PIN64(o_src); PIN32(part_st); PIN32(part_ld);
    uint4 gv;
    float oacc[2][4] = {};
    uint32_t wa[4][4][4];
    const int chb = (lane >> 3) & 1;
    {
        const float L2E = 1.4426950408889634f;
        uint32_t* const p0 = reinterpret_cast<uint32_t*>(sm + OFF_P);
        uint32_t* const p1 = reinterpret_cast<uint32_t*>(sm + OFF_P + P_PITCH * 2);
        uint4* const o_dst = &sx->o[((grp * 8 + warp) * 8 + j) * 16 + (lane >> 2)];
        if ((lane & 3) == 0) { pkt_clear(o_dst); pkt_clear(o_dst + 8); }
        float m0, m1, f0 = 1.f, f1 = 1.f;
        bar_sync(1, 256);
        {
            constexpr int NP = NA / 2;
            float e[NP][4];
#pragma unroll
            for (int i = 0; i < NP; i++) {
                const float4 v = *reinterpret_cast<const float4*>(sm + OFF_SC + (i * 32 + lane) * 16);
                e[i][0] = v.x; e[i][1] = v.y; e[i][2] = v.z; e[i][3] = v.w;
            }
            m0 = fmaxf(e[0][0], e[0][1]); m1 = fmaxf(e[0][2], e[0][3]);
#pragma unroll
            for (int i = 1; i < NP; i++) { m0 = fmaxf(m0, fmaxf(e[i][0], e[i][1])); m1 = fmaxf(m1, fmaxf(e[i][2], e[i][3])); }
#pragma unroll
            for (int o = 16; o; o >>= 1) {
                m0 = fmaxf(m0, __shfl_xor_sync(~0u, m0, o));
                m1 = fmaxf(m1, __shfl_xor_sync(~0u, m1, o));
            }
            float l0 = 0.f, l1 = 0.f;
#pragma unroll
            for (int i = 0; i < NP; i++) {
                e[i][0] = exp2f((e[i][0] - m0) * L2E); e[i][1] = exp2f((e[i][1] - m0) * L2E);
                e[i][2] = exp2f((e[i][2] - m1) * L2E); e[i][3] = exp2f((e[i][3] - m1) * L2E);
                l0 += e[i][0] + e[i][1]; l1 += e[i][2] + e[i][3];
                if (i == warp) { p0[i * 32 + lane] = pack_bf16(e[i][0], e[i][1]); p1[i * 32 + lane] = pack_bf16(e[i][2], e[i][3]); }
            }
            if (warp == 7) {
#pragma unroll
                for (int o = 16; o; o >>= 1) {
                    l0 += __shfl_xor_sync(~0u, l0, o);
                    l1 += __shfl_xor_sync(~0u, l1, o);
                }
                if (lane == 0) pkt_store(&sx->ml[cta], m0, l0, m1, l1, tag);
            }
        }
        bar_sync(1, 256);
        constexpr int NB = MB / 2;
        const uint4* const sc_src = &sx->sc[grp * MB * 128 + tid];
        const uint4* const ml_src = &sx->ml[grp * 8 + (lane & 7)];
        uint4 sv[NB], mv;
        int slot = NT % NS, ph = (NT / NS) & 1;
        const int rowl = (lane & 7) + 8 * (lane >> 4);
        const uint32_t voff = (warp >> 1) * 4096 + rowl * 128;
        const uint32_t vch0 = (((warp & 1) * 4 + chb) ^ (rowl & 7)) << 4, vch1 = (((warp & 1) * 4 + 2 + chb) ^ (rowl & 7)) << 4;
#pragma unroll 1
        for (int t = 0; t < NA; t++) {
            if (t == TSC) {
#pragma unroll
                for (int i = 0; i < NB; i++) sv[i] = pkt_load(sc_src + i * 256);
                mv = pkt_load(ml_src);
            }
            if (t == TSTAT) {
                int it = 0;
                for (;;) {
                    uint32_t bad = pkt_diff(mv, tag);
#pragma unroll
                    for (int i = 0; i < NB; i++) bad |= pkt_diff(sv[i], tag);
                    if (!(bad & 3u) || ++it >= POLL_MAX) break;
#pragma unroll
                    for (int i = 0; i < NB; i++) sv[i] = pkt_load(sc_src + i * 256);
                    mv = pkt_load(ml_src);
                }
                float e[NB][4];
                float n0 = -INFINITY, n1 = -INFINITY, l0 = 0.f, l1 = 0.f;
#pragma unroll
                for (int i = 0; i < NB; i++) {
                    e[i][0] = pkt_f(sv[i].x); e[i][1] = pkt_f(sv[i].y); e[i][2] = pkt_f(sv[i].z); e[i][3] = pkt_f(sv[i].w);
                    n0 = fmaxf(n0, fmaxf(e[i][0], e[i][1])); n1 = fmaxf(n1, fmaxf(e[i][2], e[i][3]));
                }
#pragma unroll
                for (int o = 16; o; o >>= 1) {
                    n0 = fmaxf(n0, __shfl_xor_sync(~0u, n0, o));
                    n1 = fmaxf(n1, __shfl_xor_sync(~0u, n1, o));
                }
#pragma unroll
                for (int i = 0; i < NB; i++) {
                    e[i][0] = exp2f((e[i][0] - n0) * L2E); e[i][1] = exp2f((e[i][1] - n0) * L2E);
                    e[i][2] = exp2f((e[i][2] - n1) * L2E); e[i][3] = exp2f((e[i][3] - n1) * L2E);
                    l0 += e[i][0] + e[i][1]; l1 += e[i][2] + e[i][3];
                }
#pragma unroll
                for (int o = 16; o; o >>= 1) {
                    l0 += __shfl_xor_sync(~0u, l0, o);
                    l1 += __shfl_xor_sync(~0u, l1, o);
                }
                if (lane == 0) *reinterpret_cast<float4*>(s_red + warp * 4) = make_float4(n0, l0, n1, l1);
                bar_sync(1, 256);
                float4 st = *reinterpret_cast<const float4*>(s_red + (lane & 7) * 4);
                if (lane & 8) st = make_float4(pkt_f(mv.x), pkt_f(mv.y), pkt_f(mv.z), pkt_f(mv.w));
                float M0 = st.x, M1 = st.z;
#pragma unroll
                for (int o = 8; o; o >>= 1) {
                    M0 = fmaxf(M0, __shfl_xor_sync(~0u, M0, o));
                    M1 = fmaxf(M1, __shfl_xor_sync(~0u, M1, o));
                }
                float L0 = st.y * exp2f((st.x - M0) * L2E), L1 = st.w * exp2f((st.z - M1) * L2E);
#pragma unroll
                for (int o = 8; o; o >>= 1) {
                    L0 += __shfl_xor_sync(~0u, L0, o);
                    L1 += __shfl_xor_sync(~0u, L1, o);
                }
                const float c0 = exp2f((n0 - M0) * L2E) / L0, c1 = exp2f((n1 - M1) * L2E) / L1;
                f0 = exp2f((m0 - M0) * L2E) / L0; f1 = exp2f((m1 - M1) * L2E) / L1;
#pragma unroll
                for (int i = 0; i < NB; i++) {
                    p0[NA * 16 + i * 256 + tid] = pack_bf16(e[i][0] * c0, e[i][1] * c0);
                    p1[NA * 16 + i * 256 + tid] = pack_bf16(e[i][2] * c1, e[i][3] * c1);
                }
            }
            uint32_t pb[4];
            ldB(pb, sb + OFF_P, P_PITCH * 2, t * 32, zero, lane);
            mbar_wait(sb + BAR_FULL + slot * 8, ph);
            const uint32_t base = sb + OFF_RING + slot * SLOT + voff;
#pragma unroll
            for (int ks = 0; ks < 2; ks++) {
                uint32_t a0[4], a1[4];
                ldsm4t(a0, base + ks * 2048 + vch0);
                ldsm4t(a1, base + ks * 2048 + vch1);
                mma16816(oacc[0], a0, pb[ks * 2], pb[ks * 2 + 1]);
                mma16816(oacc[1], a1, pb[ks * 2], pb[ks * 2 + 1]);
            }
            __syncwarp();
            if (lane == 0) mbar_arrive(sb + BAR_EMPTY + slot * 8, 1);
            if (++slot == NS) { slot = 0; ph ^= 1; }
        }
        if ((lane & 3) == 0) {
            pkt_store(o_dst, oacc[0][0] * f0, oacc[0][1] * f1, oacc[0][2] * f0, oacc[0][3] * f1, tag);
            pkt_store(o_dst + 8, oacc[1][0] * f0, oacc[1][1] * f1, oacc[1][2] * f0, oacc[1][3] * f1, tag);
        }
        bar_sync(1, 256);
        float o0[4] = {}, o1[4] = {}, o2[4] = {}, o3[4] = {};
        uint4 oa, ob;
        const int row2 = (warp >> 1) * 64 + (lane & 7) + 8 * (lane >> 4);
        const uint32_t voff2 = row2 * 64 + (((2 * (warp & 1) + chb) ^ ((row2 >> 1) & 3)) << 4);
#pragma unroll
        for (int t = NA; t < NT; t++) {
            if (t == TO) { oa = pkt_load(o_src); ob = pkt_load(o_src + 16); }
            if (t == NT - 1) {
                int it = 0;
                while (((pkt_diff(oa, tag) | pkt_diff(ob, tag)) & 3u) && ++it < POLL_MAX) { oa = pkt_load(o_src); ob = pkt_load(o_src + 16); }
                o0[0] += pkt_f(oa.x); o0[1] += pkt_f(oa.y); o0[2] += pkt_f(oa.z); o0[3] += pkt_f(oa.w);
                o1[0] += pkt_f(ob.x); o1[1] += pkt_f(ob.y); o1[2] += pkt_f(ob.z); o1[3] += pkt_f(ob.w);
            }
            if (t == TWO && warp < 7) {
                gv = pkt_load(g_src);
            }
            if (t == TWO && warp < 6) {
                mbar_wait(sb + BAR_WO + warp * 8, 0);
#pragma unroll
                for (int ks = 0; ks < 4; ks++)
#pragma unroll
                    for (int mt = 0; mt < 4; mt++) ldsm4t(wa[mt][ks], wo_addr[mt] + ks * 2048);
            }
            uint32_t pb[2][4];
            ldB(pb[0], sb + OFF_P, P_PITCH * 2, NA * 32 + (t - NA) * 256 + (warp >> 1) * 64, zero, lane);
            ldB(pb[1], sb + OFF_P, P_PITCH * 2, NA * 32 + (t - NA) * 256 + (warp >> 1) * 64 + 32, zero, lane);
            mbar_wait(sb + BAR_FULL + ((NT + t) % NS) * 8, ((NT + t) / NS) & 1);
            const uint32_t base = sb + OFF_RING + ((NT + t) % NS) * SLOT + voff2;
            uint32_t a[4][4];
            ldsm4t(a[0], base); ldsm4t(a[1], base + 1024); ldsm4t(a[2], base + 2048); ldsm4t(a[3], base + 3072);
            mma16816(o0, a[0], pb[0][0], pb[0][1]);
            mma16816(o1, a[1], pb[0][2], pb[0][3]);
            mma16816(o2, a[2], pb[1][0], pb[1][1]);
            mma16816(o3, a[3], pb[1][2], pb[1][3]);
        }
        sts128_if((lane & 3) == 0, part_st, (o0[0] + o1[0]) + (o2[0] + o3[0]), (o0[1] + o1[1]) + (o2[1] + o3[1]),
                  (o0[2] + o1[2]) + (o2[2] + o3[2]), (o0[3] + o1[3]) + (o2[3] + o3[3]));
    }
    if (warp == 7) { bar_arrive(2, 256); return; }
    bar_sync(2, 256);
    const float2 v0 = lds64(part_ld), v1 = lds64(part_ld + 256), v2 = lds64(part_ld + 512), v3 = lds64(part_ld + 768);
    const uint32_t ow = pack_bf16((v0.x + v1.x) + (v2.x + v3.x), (v0.y + v1.y) + (v2.y + v3.y));
    if (warp == 6) {
        mbar_wait(sb + BAR_WO + warp * 8, 0);
#pragma unroll
        for (int ks = 0; ks < 4; ks++)
#pragma unroll
            for (int mt = 0; mt < 4; mt++) ldsm4t(wa[mt][ks], wo_addr[mt] + ks * 2048);
    }
    float acc[2][4][4] = {};
#pragma unroll
    for (int ks = 0; ks < 4; ks++) {
        const uint32_t b0 = __shfl_sync(~0u, ow, ks * 8 + (lane & 3));
        const uint32_t b1 = __shfl_sync(~0u, ow, ks * 8 + 4 + (lane & 3));
#pragma unroll
        for (int mt = 0; mt < 4; mt++) mma16816(acc[ks & 1][mt], wa[mt][ks], b0, b1);
    }
    const int t4 = lane & 3;
    float sum[8];
#pragma unroll
    for (int mt = 0; mt < 4; mt++) { sum[2 * mt] = acc[0][mt][0] + acc[1][mt][0]; sum[2 * mt + 1] = acc[0][mt][2] + acc[1][mt][2]; }
    const float a0 = fsel(t4 == 0, sum[0], fsel(t4 == 1, sum[3], sum[6]));
    const float a1 = fsel(t4 == 0, sum[1], fsel(t4 == 1, sum[4], sum[7]));
    const float a2 = fsel(t4 == 0, sum[2], fsel(t4 == 1, sum[5], 0.f));
    if (t4 < 3) {
        float o0, o1, o2, cnt;
        asm volatile("atom.relaxed.gpu.global.add.v4.f32 {%0,%1,%2,%3}, [%4], {%5,%6,%7,%8};"
                     : "=f"(o0), "=f"(o1), "=f"(o2), "=f"(cnt) : "l"(acc_dst), "f"(a0), "f"(a1), "f"(a2), "f"(1.0f) : "memory");
        if (cnt == 63.f) {
            int it = 0;
            while ((pkt_diff(gv, tag) & 3u) && ++it < POLL_MAX) gv = pkt_load(g_src);
            const uint32_t r01 = pack_bf16(xq[0] + bf16r(bf16r(o0 + a0) * pkt_f(gv.x)), xq[1] + bf16r(bf16r(o1 + a1) * pkt_f(gv.y)));
            const uint32_t r2 = pack_bf16(xq[2] + bf16r(bf16r(o2 + a2) * pkt_f(gv.z)), 0.f);
            asm volatile("st.global.u16 [%0], %1;" :: "l"(out_dst), "h"((unsigned short)r01) : "memory");
            asm volatile("st.global.u16 [%0+16], %1;" :: "l"(out_dst), "h"((unsigned short)(r01 >> 16)) : "memory");
            if (t4 < 2) asm volatile("st.global.u16 [%0+32], %1;" :: "l"(out_dst), "h"((unsigned short)r2) : "memory");
        }
    }
}

typedef CUresult (*EncodeFn)(CUtensorMap*, CUtensorMapDataType, cuuint32_t, void*, const cuuint64_t*, const cuuint64_t*,
                             const cuuint32_t*, const cuuint32_t*, CUtensorMapInterleave, CUtensorMapSwizzle,
                             CUtensorMapL2promotion, CUtensorMapFloatOOBfill);

void make_map(EncodeFn enc, CUtensorMap* m, const void* ptr, uint64_t cols, uint64_t rows, uint32_t bc, uint32_t br,
              CUtensorMapSwizzle sw) {
    cuuint64_t dims[2] = {cols, rows};
    cuuint64_t strides[1] = {cols * 2};
    cuuint32_t box[2] = {bc, br};
    cuuint32_t es[2] = {1, 1};
    enc(m, CU_TENSOR_MAP_DATA_TYPE_BFLOAT16, 2, const_cast<void*>(ptr), dims, strides, box, es,
        CU_TENSOR_MAP_INTERLEAVE_NONE, sw, CU_TENSOR_MAP_L2_PROMOTION_L2_128B, CU_TENSOR_MAP_FLOAT_OOB_FILL_NONE);
}

}

extern "C" void kernel_launch(void* const* d_in, const int* in_sizes, int n_in, void* d_out, int out_size) {
    (void)in_sizes; (void)n_in; (void)out_size;
    static EncodeFn enc = nullptr;
    static Scratch* scratch = nullptr;
    if (!enc) {
        void* fn = nullptr;
        cudaDriverEntryPointQueryResult qr;
        cudaGetDriverEntryPoint("cuTensorMapEncodeTiled", &fn, cudaEnableDefault, &qr);
        enc = (EncodeFn)fn;
        cudaGetSymbolAddress((void**)&scratch, g_scratch);
        cudaFuncSetAttribute(fused_decode_kernel, cudaFuncAttributeMaxDynamicSharedMemorySize, SMEM_BYTES);
    }
    Params p;
    p.k = (const uint8_t*)d_in[1];
    p.wq_raw = (const uint8_t*)d_in[3];
    p.x = (const __nv_bfloat16*)d_in[0];
    p.out = (__nv_bfloat16*)d_out;
    p.sx = scratch;
    make_map(enc, &p.v,  d_in[2], 256,  (uint64_t)16 * SK, 32, 256, CU_TENSOR_MAP_SWIZZLE_64B);
    {
        cuuint64_t dims[3] = {64, (cuuint64_t)16 * SK, 4};
        cuuint64_t strides[2] = {512, 128};
        cuuint32_t box[3] = {64, 32, 4};
        cuuint32_t es[3] = {1, 1, 1};
        enc(&p.va, CU_TENSOR_MAP_DATA_TYPE_BFLOAT16, 3, d_in[2], dims, strides, box, es, CU_TENSOR_MAP_INTERLEAVE_NONE,
            CU_TENSOR_MAP_SWIZZLE_128B, CU_TENSOR_MAP_L2_PROMOTION_NONE, CU_TENSOR_MAP_FLOAT_OOB_FILL_NONE);
    }
    make_map(enc, &p.wq, d_in[3], 4096, D,  64, 224, CU_TENSOR_MAP_SWIZZLE_128B);
    {
        cuuint64_t dims[5] = {D, 16, 2, 8, 16};
        cuuint64_t strides[4] = {256 * D * 2, 8 * D * 2, D * 2, 16 * D * 2};
        cuuint32_t box[5] = {64, 2, 2, 8, 2};
        cuuint32_t es[5] = {1, 1, 1, 1, 1};
        enc(&p.wo, CU_TENSOR_MAP_DATA_TYPE_BFLOAT16, 5, d_in[4], dims, strides, box, es, CU_TENSOR_MAP_INTERLEAVE_NONE,
            CU_TENSOR_MAP_SWIZZLE_128B, CU_TENSOR_MAP_L2_PROMOTION_L2_128B, CU_TENSOR_MAP_FLOAT_OOB_FILL_NONE);
    }
    make_map(enc, &p.wg, d_in[6], FF,   D,  64, 224, CU_TENSOR_MAP_SWIZZLE_128B);
    make_map(enc, &p.wu, d_in[7], FF,   D,  64, 224, CU_TENSOR_MAP_SWIZZLE_128B);
    make_map(enc, &p.wd, d_in[8], D,    FF, 64, 128, CU_TENSOR_MAP_SWIZZLE_128B);
    fused_decode_kernel<<<NCTA, NTHREADS, SMEM_BYTES, cudaStreamPerThread>>>(p);
}
```

```cpp
#include <cuda_runtime.h>
#include <cuda_bf16.h>
#include <cuda.h>
#include <stdint.h>

namespace {

constexpr int D = 448, SK = 32768, WIN = 4096, FF = 1792;
constexpr int NMAIN = 128, NHELP = 4, NCTA = NMAIN + NHELP;
constexpr int NS = 9;
constexpr int SLOT = 16384;
constexpr int NT = 16;
constexpr int NTHREADS = 288;

constexpr int MB = 4, NA = NT - MB;
constexpr int KDEPTH = 3;
constexpr int VDEPTH = 2;
constexpr int NSTART = 2;
constexpr int GUPOS = 5;
constexpr int GUT = 6;
constexpr int WOPOS = 19;
constexpr int TSC = 7, TSTAT = 9;
constexpr int TWO = 13;
constexpr int TO = 14;

constexpr int OFF_RING = 0;
constexpr int OFF_W    = OFF_RING + NS * SLOT;
constexpr int OFF_P    = OFF_W + 57344;
constexpr int P_PITCH  = NA * 32 + MB * 256 + 8;
constexpr int OFF_SC   = OFF_P + 2 * P_PITCH * 2;
constexpr int OFF_XN   = OFF_SC + NA * 256;
constexpr int XN_PITCH = 456;
constexpr int OFF_Q    = OFF_XN + 2 * XN_PITCH * 2;
constexpr int OFF_ZERO = OFF_Q + 1024;
constexpr int OFF_PART = OFF_ZERO + 16;
constexpr int OFF_PART2 = OFF_PART + 2048;
constexpr int OFF_RED  = OFF_PART2 + 1024;
constexpr int OFF_TAG  = OFF_RED + 128;
constexpr int OFF_BAR  = OFF_TAG + 16;
constexpr int BAR_FULL = OFF_BAR, BAR_EMPTY = BAR_FULL + NS * 8;
constexpr int BAR_WQ = BAR_EMPTY + NS * 8, BAR_GU = BAR_WQ + 8, BAR_WO = BAR_GU + 8, BAR_WFREE = BAR_WO + 7 * 8;
constexpr int SMEM_BYTES = BAR_WFREE + 8 + 1024;
constexpr int H_PITCH = FF + 8;
static_assert(OFF_XN % 16 == 0 && OFF_Q % 16 == 0 && OFF_P % 16 == 0 && OFF_PART % 16 == 0 && OFF_BAR % 8 == 0, "align");
static_assert(SMEM_BYTES <= 232448, "smem");

struct __align__(4096) Scratch {
    float4 acc[2][2][256];
    uint4 sc[16 * MB * 128];
    uint4 o[NMAIN * 8 * 16];
    uint4 ml[NMAIN];
    uint4 q[NMAIN * 32];
    uint4 h[112 * 32];
    uint4 g[2 * 7 * 32];
    unsigned epoch[NCTA];
};
__device__ Scratch g_scratch;

struct Params {
    const uint8_t* wq_raw;
    const uint8_t* k;
    const __nv_bfloat16* x;
    __nv_bfloat16* out;
    Scratch* sx;
    alignas(64) CUtensorMap wq;
    CUtensorMap v, va, wg, wu, wo, wd;
};

__device__ __forceinline__ uint32_t smem_u32(const void* p) { return (uint32_t)__cvta_generic_to_shared(p); }
__device__ __forceinline__ bool elect_one() {
    uint32_t p;
    asm volatile("{\n.reg .pred P;\nelect.sync _|P, 0xffffffff;\nselp.u32 %0, 1, 0, P;\n}" : "=r"(p));
    return p;
}
__device__ __forceinline__ void mbar_init(uint32_t bar, uint32_t cnt) {
    asm volatile("mbarrier.init.shared::cta.b64 [%0], %1;" :: "r"(bar), "r"(cnt) : "memory");
}
__device__ __forceinline__ void mbar_expect_tx(uint32_t bar, uint32_t bytes) {
    asm volatile("mbarrier.arrive.expect_tx.shared::cta.b64 _, [%0], %1;" :: "r"(bar), "r"(bytes) : "memory");
}
__device__ __forceinline__ void mbar_arrive(uint32_t bar, uint32_t cnt) {
    asm volatile("mbarrier.arrive.shared::cta.b64 _, [%0], %1;" :: "r"(bar), "r"(cnt) : "memory");
}
__device__ __forceinline__ void mbar_wait(uint32_t bar, uint32_t parity) {
    uint32_t ok;
    int it = 0;
    do {
        asm volatile("{\n.reg .pred p;\nmbarrier.test_wait.parity.shared::cta.b64 p, [%1], %2;\nselp.u32 %0, 1, 0, p;\n}"
                     : "=r"(ok) : "r"(bar), "r"(parity) : "memory");
    } while (!ok && ++it < (1 << 24));
}
__device__ __forceinline__ void bulk1d(uint32_t dst, const void* src, uint32_t bytes, uint32_t bar, uint64_t pol) {
    asm volatile("cp.async.bulk.shared::cluster.global.mbarrier::complete_tx::bytes.L2::cache_hint [%0], [%1], %2, [%3], %4;"
                 :: "r"(dst), "l"(src), "r"(bytes), "r"(bar), "l"(pol) : "memory");
}
__device__ __forceinline__ void tma2d(uint32_t dst, const CUtensorMap* map, int c0, int c1, uint32_t bar, uint64_t pol) {
    asm volatile("cp.async.bulk.tensor.2d.shared::cluster.global.mbarrier::complete_tx::bytes.L2::cache_hint [%0], [%1, {%3, %4}], [%2], %5;"
                 :: "r"(dst), "l"(map), "r"(bar), "r"(c0), "r"(c1), "l"(pol) : "memory");
}
__device__ __forceinline__ void tma3d(uint32_t dst, const CUtensorMap* map, int c1, uint32_t bar, uint64_t pol) {
    asm volatile("cp.async.bulk.tensor.3d.shared::cluster.global.mbarrier::complete_tx::bytes.L2::cache_hint [%0], [%1, {%4, %3, %4}], [%2], %5;"
                 :: "r"(dst), "l"(map), "r"(bar), "r"(c1), "r"(0), "l"(pol) : "memory");
}
__device__ __forceinline__ void tma5d(uint32_t dst, const CUtensorMap* map, int c0, int c1, int c4, uint32_t bar, uint64_t pol) {
    asm volatile("cp.async.bulk.tensor.5d.shared::cluster.global.mbarrier::complete_tx::bytes.L2::cache_hint [%0], [%1, {%3, %4, %6, %6, %5}], [%2], %7;"
                 :: "r"(dst), "l"(map), "r"(bar), "r"(c0), "r"(c1), "r"(c4), "r"(0), "l"(pol) : "memory");
}
__device__ __forceinline__ void ldsm4(uint32_t (&r)[4], uint32_t addr) {
    asm volatile("ldmatrix.sync.aligned.m8n8.x4.shared.b16 {%0,%1,%2,%3}, [%4];"
                 : "=r"(r[0]), "=r"(r[1]), "=r"(r[2]), "=r"(r[3]) : "r"(addr) : "memory");
}
__device__ __forceinline__ void ldsm4t(uint32_t (&r)[4], uint32_t addr) {
    asm volatile("ldmatrix.sync.aligned.m8n8.x4.trans.shared.b16 {%0,%1,%2,%3}, [%4];"
                 : "=r"(r[0]), "=r"(r[1]), "=r"(r[2]), "=r"(r[3]) : "r"(addr) : "memory");
}
__device__ __forceinline__ void lds128(uint32_t (&r)[4], uint32_t addr) {
    asm volatile("ld.shared.v4.u32 {%0,%1,%2,%3}, [%4];"
                 : "=r"(r[0]), "=r"(r[1]), "=r"(r[2]), "=r"(r[3]) : "r"(addr) : "memory");
}
__device__ __forceinline__ void sts128_if(bool c, uint32_t addr, float x, float y, float z, float w) {
    asm volatile("{\n.reg .pred p;\nsetp.ne.u32 p, %5, 0;\n@p st.shared.v4.f32 [%0], {%1,%2,%3,%4};\n}"
                 :: "r"(addr), "f"(x), "f"(y), "f"(z), "f"(w), "r"((uint32_t)c) : "memory");
}
__device__ __forceinline__ float2 lds64(uint32_t addr) {
    float2 v;
    asm volatile("ld.shared.v2.f32 {%0,%1}, [%2];" : "=f"(v.x), "=f"(v.y) : "r"(addr) : "memory");
    return v;
}
#define PIN32(x) asm volatile("" : "+r"(x))
#define PIN64(x) asm volatile("" : "+l"(x))
__device__ __forceinline__ void mma16816(float (&c)[4], uint32_t a0, uint32_t a1, uint32_t a2, uint32_t a3, uint32_t b0, uint32_t b1) {
    asm volatile("mma.sync.aligned.m16n8k16.row.col.f32.bf16.bf16.f32 {%0,%1,%2,%3}, {%4,%5,%6,%7}, {%8,%9}, {%0,%1,%2,%3};"
                 : "+f"(c[0]), "+f"(c[1]), "+f"(c[2]), "+f"(c[3])
                 : "r"(a0), "r"(a1), "r"(a2), "r"(a3), "r"(b0), "r"(b1));
}
__device__ __forceinline__ void mma16816(float (&c)[4], const uint32_t (&a)[4], uint32_t b0, uint32_t b1) {
    mma16816(c, a[0], a[1], a[2], a[3], b0, b1);
}
__device__ __forceinline__ void bar_sync(int id, int n) { asm volatile("bar.sync %0, %1;" :: "r"(id), "r"(n) : "memory"); }
__device__ __forceinline__ void bar_arrive(int id, int n) { asm volatile("bar.arrive %0, %1;" :: "r"(id), "r"(n) : "memory"); }
__device__ __forceinline__ uint32_t pack_bf16(float lo, float hi) {
    uint32_t r;
    asm("cvt.rn.bf16x2.f32 %0, %1, %2;" : "=r"(r) : "f"(hi), "f"(lo));
    return r;
}
__device__ __forceinline__ float bf16r(float v) { return __uint_as_float(pack_bf16(0.f, v)); }

__device__ __forceinline__ float fsel(bool c, float a, float b) {
    float r;
    asm("{\n.reg .pred p;\nsetp.ne.u32 p, %3, 0;\nselp.f32 %0, %1, %2, p;\n}" : "=f"(r) : "f"(a), "f"(b), "r"((uint32_t)c));
    return r;
}

__device__ __forceinline__ __nv_bfloat16 geglu(float gate, float up) {
    const float ga = bf16r(gate);
    const float in = 0.7978845608028654f * (ga + 0.044715f * ga * ga * ga);
    return __float2bfloat16_rn(bf16r(0.5f * ga * (1.0f + tanhf(in))) * bf16r(up));
}

__device__ __forceinline__ void ldB(uint32_t (&r)[4], uint32_t base, int pitch_bytes, int k0, uint32_t zero, int lane) {
    const int n = lane & 7;
    ldsm4(r, n < 2 ? base + n * pitch_bytes + (k0 + 8 * (lane >> 3)) * 2 : zero);
}

__device__ __forceinline__ void pkt_store(uint4* p, float a, float b, float c, float d, uint32_t tag) {
    const uint32_t w0 = (__float_as_uint(a) & ~3u) | (tag & 3u);
    const uint32_t w1 = (__float_as_uint(b) & ~3u) | ((tag >> 2) & 3u);
    const uint32_t w2 = (__float_as_uint(c) & ~3u) | ((tag >> 4) & 3u);
    const uint32_t w3 = (__float_as_uint(d) & ~3u) | ((tag >> 6) & 3u);
    asm volatile("{\n.reg .b128 t;\n.reg .b64 lo, hi;\nmov.b64 lo, {%1, %2};\nmov.b64 hi, {%3, %4};\nmov.b128 t, {lo, hi};\n"
                 "st.relaxed.gpu.global.b128 [%0], t;\n}"
                 :: "l"(p), "r"(w0), "r"(w1), "r"(w2), "r"(w3) : "memory");
}
__device__ __forceinline__ void pkt_clear(uint4* p) { pkt_store(p, 0.f, 0.f, 0.f, 0.f, 0); }
__device__ __forceinline__ uint4 pkt_load(const uint4* p) {
    uint4 v;
    asm volatile("{\n.reg .b128 t;\n.reg .b64 lo, hi;\nld.relaxed.gpu.global.b128 t, [%4];\nmov.b128 {lo, hi}, t;\n"
                 "mov.b64 {%0, %1}, lo;\nmov.b64 {%2, %3}, hi;\n}"
                 : "=r"(v.x), "=r"(v.y), "=r"(v.z), "=r"(v.w) : "l"(p) : "memory");
    return v;
}
__device__ __forceinline__ uint32_t pkt_diff(const uint4& v, uint32_t tag) {
    return ((v.x ^ tag) | (v.y ^ (tag >> 2))) | ((v.z ^ (tag >> 4)) | (v.w ^ (tag >> 6)));
}
__device__ __forceinline__ float pkt_f(uint32_t w) { return __uint_as_float(w & ~3u); }
constexpr int POLL_MAX = 1 << 20;

__global__ void __launch_bounds__(NTHREADS, 1) fused_decode_kernel(const __grid_constant__ Params prm) {
    extern __shared__ uint8_t smem_raw[];
    const int cta = blockIdx.x;
    const int tid = threadIdx.x, lane = tid & 31;
    const bool is_main = cta < NMAIN;
    if (tid == 0 && is_main) {
        uint64_t pol;
        asm volatile("createpolicy.fractional.L2::evict_normal.b64 %0, 1.0;" : "=l"(pol));
        asm volatile("cp.async.bulk.prefetch.L2.global.L2::cache_hint [%0], %1, %2;"
                     :: "l"(prm.wq_raw + cta * 28672), "r"(28672), "l"(pol) : "memory");
    }
    const int warp = __shfl_sync(~0u, tid >> 5, 0);

    const uint32_t sb = (smem_u32(smem_raw) + 1023u) & ~1023u;
    const int grp = cta >> 3, j = cta & 7;
    const int b = grp >> 3;
    const bool has_ffn = is_main && j < 7;
    const int fblk = grp * 7 + j;
    const int qblk = (grp & 7) * 16 + b * 8 + j;
    const int ncg = is_main ? 0 : (cta - NMAIN < 3 ? 2 : 1);
    const int cg0 = (cta - NMAIN) * 2;
    Scratch* const sx = prm.sx;
    uint8_t* const sm = smem_raw + (sb - smem_u32(smem_raw));
    volatile uint32_t* const s_tag = reinterpret_cast<volatile uint32_t*>(sm + OFF_TAG);

    if (warp == 8 && elect_one()) {
        uint64_t pol, npol;
        asm volatile("createpolicy.fractional.L2::evict_first.b64 %0, 1.0;" : "=l"(pol));
        asm volatile("createpolicy.fractional.L2::evict_normal.b64 %0, 1.0;" : "=l"(npol));
        const uint8_t* const ksrc = prm.k + (uint32_t)((grp * SK + (SK - WIN) + j * 32) * 512);
#pragma unroll
        for (int i = 0; i < NSTART; i++) mbar_init(sb + BAR_FULL + i * 8, 1);
        mbar_init(sb + BAR_WQ, 1);
        asm volatile("fence.mbarrier_init.release.cluster;" ::: "memory");
        if (is_main) {
            mbar_expect_tx(sb + BAR_WQ, 28672);
            tma2d(sb + OFF_W, &prm.wq, (qblk >> 1) * 64, (qblk & 1) * 224, sb + BAR_WQ, npol);
#pragma unroll
            for (int i = 0; i < NSTART; i++) {
                mbar_expect_tx(sb + BAR_FULL + i * 8, SLOT);
                bulk1d(sb + OFF_RING + i * SLOT, ksrc + (size_t)i * 256 * 512, SLOT, sb + BAR_FULL + i * 8, pol);
            }
        }
#pragma unroll
        for (int i = NSTART; i < NS; i++) mbar_init(sb + BAR_FULL + i * 8, 1);
#pragma unroll
        for (int i = 0; i < NS; i++) mbar_init(sb + BAR_EMPTY + i * 8, 8);
        mbar_init(sb + BAR_GU, 1); mbar_init(sb + BAR_WFREE, 8);
#pragma unroll
        for (int c = 0; c < 7; c++) mbar_init(sb + BAR_WO + c * 8, 1);
        asm volatile("fence.mbarrier_init.release.cluster;" ::: "memory");
    }

    const uint32_t zero = sb + OFF_ZERO;
    float* const s_part = reinterpret_cast<float*>(sm + OFF_PART);
    float* const s_red = reinterpret_cast<float*>(sm + OFF_RED);
    uint32_t xw[7];
    if (warp < 2 && is_main) {
        const uint32_t* xp = reinterpret_cast<const uint32_t*>(prm.x + warp * D);
#pragma unroll
        for (int i = 0; i < 7; i++) xw[i] = __ldg(xp + lane + 32 * i);
    }
    unsigned epoch = 0;
    if (tid == 64) epoch = sx->epoch[cta];
    if (tid == 96) *reinterpret_cast<uint4*>(sm + OFF_ZERO) = make_uint4(0, 0, 0, 0);
    if (is_main) {
        if (warp == 4) pkt_clear(&sx->q[qblk * 32 + lane]);
        if (warp == 5 && has_ffn) pkt_clear(&sx->h[fblk * 32 + lane]);
    } else if (warp < ncg * 2) {
        pkt_clear(&sx->g[((warp & 1) * 7 + cg0 + (warp >> 1)) * 32 + lane]);
    }
    __syncthreads();

    if (warp == 8) {
        const bool leader = elect_one();
        int ucta;
        asm volatile("mov.u32 %0, %%ctaid.x;" : "=r"(ucta));
        const uint8_t* const ksrc = prm.k + (uint32_t)(((ucta >> 3) * SK + (SK - WIN) + (ucta & 7) * 32) * 512);
        uint64_t pol, npol;
        asm volatile("createpolicy.fractional.L2::evict_first.b64 %0, 1.0;" : "=l"(pol));
        asm volatile("createpolicy.fractional.L2::evict_normal.b64 %0, 1.0;" : "=l"(npol));
        if (is_main) {
            if (leader) {
                asm volatile("prefetch.tensormap [%0];" :: "l"((fblk & 1) ? &prm.wu : &prm.wg) : "memory");
                asm volatile("prefetch.tensormap [%0];" :: "l"(&prm.va) : "memory");
                asm volatile("prefetch.tensormap [%0];" :: "l"(&prm.v) : "memory");
                asm volatile("prefetch.tensormap [%0];" :: "l"(&prm.wo) : "memory");
            }
            const int vrow = (ucta >> 3) * SK + (SK - WIN), vcol = (ucta & 7) * 32, wohead = ((ucta >> 3) & 7) * 2, woblk = (ucta & 7) * 2;
            uint32_t so = NSTART * 8, eph = 1, lo = 0, lph = 0;
            auto acquire = [&](int n) {
                if (n >= NS) mbar_wait(sb + BAR_EMPTY + so, eph);
                if (leader) mbar_expect_tx(sb + BAR_FULL + so, SLOT);
            };
            auto landing = [&]() {
                mbar_wait(sb + BAR_FULL + lo, lph);
            };
            auto advance = [&](bool l) {
                so += 8; if (so == NS * 8) { so = 0; eph ^= 1; }
                if (l) { lo += 8; if (lo == NS * 8) { lo = 0; lph ^= 1; } }
            };
            acquire(NSTART);
            mbar_wait(sb + BAR_WQ, 0);
            if (leader) bulk1d(sb + OFF_RING + so * (SLOT / 8), ksrc + NSTART * 256 * 512, SLOT, sb + BAR_FULL + so, pol);
            advance(false);
            const uint8_t* src = ksrc + (NSTART + 1) * 256 * 512;
#pragma unroll 1
            for (int n = NSTART + 1; n < NT; n++) {
                acquire(n);
                const uint32_t bar = sb + BAR_FULL + so, dst = sb + OFF_RING + so * (SLOT / 8);
                landing();
                if (leader) bulk1d(dst, src, SLOT, bar, pol);
                if (n == GUPOS && has_ffn && leader) {
                    mbar_expect_tx(sb + BAR_GU, 28672);
                    tma2d(sb + OFF_W + 28672, (fblk & 1) ? &prm.wu : &prm.wg, (fblk >> 2) * 64, ((fblk >> 1) & 1) * 224, sb + BAR_GU, npol);
                }
                src += 256 * 512;
                advance(true);
            }
            int row = vrow + vcol;
#pragma unroll 1
            for (int n = NT; n < NT + NA; n++) {
                acquire(n);
                if (n == WOPOS) mbar_wait(sb + BAR_WFREE, 0);
                const uint32_t bar = sb + BAR_FULL + so, dst = sb + OFF_RING + so * (SLOT / 8);
                landing();
                if (leader) tma3d(dst, &prm.va, row, bar, pol);
                if (n >= WOPOS && n < WOPOS + 6 && leader) {
                    const int c = n - WOPOS;
                    mbar_expect_tx(sb + BAR_WO + c * 8, 8192);
                    tma5d(sb + OFF_W + c * 8192, &prm.wo, c * 64, wohead, woblk, sb + BAR_WO + c * 8, npol);
                }
                row += 256;
                advance(true);
            }
            static_assert(KDEPTH == NSTART + 1 && VDEPTH == KDEPTH - 1 && WOPOS >= NT && WOPOS + 7 <= NT + NA, "producer loops");
            row = vrow + NA * 256;
            landing();
            lo += 8; if (lo == NS * 8) { lo = 0; lph ^= 1; }
#pragma unroll 1
            for (int n = NT + NA; n < 2 * NT; n++) {
                acquire(n);
                const uint32_t bar = sb + BAR_FULL + so, dst = sb + OFF_RING + so * (SLOT / 8);
                landing();
                if (leader) tma2d(dst, &prm.v, vcol, row, bar, pol);
                row += 256;
                advance(true);
            }
            if (leader) mbar_expect_tx(sb + BAR_WO + 6 * 8, 8192);
            landing();
            if (leader) tma5d(sb + OFF_W + 6 * 8192, &prm.wo, 6 * 64, wohead, woblk, sb + BAR_WO + 6 * 8, npol);
        } else {
            int slot = 0, ph = 1;
            for (int n = 0; n < 14 * ncg; n++) {
                if (n >= NS) mbar_wait(sb + BAR_EMPTY + slot * 8, ph);
                if (leader) {
                    mbar_expect_tx(sb + BAR_FULL + slot * 8, SLOT);
                    tma2d(sb + OFF_RING + slot * SLOT, &prm.wd, (cg0 + (ncg == 2 ? (n & 1) : 0)) * 64, (ncg == 2 ? (n >> 1) : n) * 128,
                          sb + BAR_FULL + slot * 8, npol);
                }
                if (++slot == NS) { slot = 0; ph ^= 1; }
            }
        }
        return;
    }

    if (!is_main) {
        if (tid == 64) { sx->epoch[cta] = epoch + 1; s_tag[0] = epoch % 255u + 1u; s_tag[1] = epoch; }
        bar_sync(1, 256);
        const uint32_t tag = s_tag[0];
        if (warp < 3) {
            const int i = (cta - NMAIN) * 3 + warp;
            sx->acc[(s_tag[1] + 1) & 1][i / 6][(i % 6) * 32 + lane] = make_float4(0.f, 0.f, 0.f, 0.f);
        }
        __nv_bfloat16* h_s = reinterpret_cast<__nv_bfloat16*>(sm + OFF_W);
        {
            uint4 v[4][4];
            const int ncb = warp < 4 ? 4 : 3;
            int it = 0;
            uint32_t bad;
            do {
                if (it) __nanosleep(200);
                bad = 0;
#pragma unroll
                for (int i = 0; i < 4; i++)
#pragma unroll
                    for (int q = 0; q < 4; q++)
                        if (i < ncb) v[i][q] = pkt_load(&sx->h[(warp + 8 * i) * 128 + q * 32 + lane]);
#pragma unroll
                for (int i = 0; i < 4; i++)
                    if (i < ncb) bad |= (pkt_diff(v[i][0], tag) | pkt_diff(v[i][1], tag)) | (pkt_diff(v[i][2], tag) | pkt_diff(v[i][3], tag));
            } while ((bad & 3u) && ++it < POLL_MAX);
#pragma unroll
            for (int i = 0; i < 4; i++) {
                if (i < ncb) {
                    __nv_bfloat16* dst = h_s + (warp + 8 * i) * 64 + (lane >> 3) * 16 + (lane & 7);
                    dst[0]           = geglu(pkt_f(v[i][0].x) + pkt_f(v[i][2].x), pkt_f(v[i][1].x) + pkt_f(v[i][3].x));
                    dst[H_PITCH]     = geglu(pkt_f(v[i][0].y) + pkt_f(v[i][2].y), pkt_f(v[i][1].y) + pkt_f(v[i][3].y));
                    dst[8]           = geglu(pkt_f(v[i][0].z) + pkt_f(v[i][2].z), pkt_f(v[i][1].z) + pkt_f(v[i][3].z));
                    dst[H_PITCH + 8] = geglu(pkt_f(v[i][0].w) + pkt_f(v[i][2].w), pkt_f(v[i][1].w) + pkt_f(v[i][3].w));
                }
            }
        }
        bar_sync(1, 256);
        const int mt = warp & 3, kh = warp >> 2;
        float acc[2][4] = {};
        int slot = 0, ph = 0;
        for (int rb = 0; rb < 14; rb++) {
            uint32_t bf[2][4];
            ldB(bf[0], sb + OFF_W, H_PITCH * 2, rb * 128 + kh * 64, zero, lane);
            ldB(bf[1], sb + OFF_W, H_PITCH * 2, rb * 128 + kh * 64 + 32, zero, lane);
#pragma unroll
            for (int ci = 0; ci < 2; ci++) {
                if (ci < ncg) {
                    mbar_wait(sb + BAR_FULL + slot * 8, ph);
                    const uint32_t base = sb + OFF_RING + slot * SLOT;
#pragma unroll
                    for (int ks = 0; ks < 4; ks++) {
                        const int row = kh * 64 + ks * 16 + (lane & 7) + 8 * (lane >> 4);
                        const int ch = 2 * mt + ((lane >> 3) & 1);
                        uint32_t a[4];
                        ldsm4t(a, base + row * 128 + ((ch ^ (row & 7)) << 4));
                        mma16816(acc[ci], a, bf[ks >> 1][(ks & 1) * 2], bf[ks >> 1][(ks & 1) * 2 + 1]);
                    }
                    __syncwarp();
                    if (lane == 0) mbar_arrive(sb + BAR_EMPTY + slot * 8, 1);
                    if (++slot == NS) { slot = 0; ph ^= 1; }
                }
            }
        }
        if ((lane & 3) == 0) {
#pragma unroll
            for (int ci = 0; ci < 2; ci++) {
                float* p = s_part + kh * 256 + ci * 128 + (mt * 16 + (lane >> 2)) * 2;
                p[0] = acc[ci][0]; p[1] = acc[ci][1]; p[16] = acc[ci][2]; p[17] = acc[ci][3];
            }
        }
        bar_sync(1, 256);
        if (warp < ncg * 2) {
            const int ci = warp >> 1, bb = warp & 1;
            float g[3];
#pragma unroll
            for (int i = 0; i < 3; i++) {
                const int col = ((lane >> 2) + 8 * (3 * (lane & 3) + i)) & 63;
                const float y = bf16r(s_part[ci * 128 + col * 2 + bb] + s_part[256 + ci * 128 + col * 2 + bb]);
                g[i] = bf16r(y / (1.0f + expf(-y)));
            }
            pkt_store(&sx->g[(bb * 7 + cg0 + ci) * 32 + lane], g[0], g[1], g[2], 0.f, tag);
        }
        return;
    }

    if (warp < 2) {
        float xv[14], sum = 0.f;
#pragma unroll
        for (int i = 0; i < 7; i++) {
            xv[2 * i] = __uint_as_float(xw[i] << 16);
            xv[2 * i + 1] = __uint_as_float(xw[i] & 0xffff0000u);
            sum += xv[2 * i] + xv[2 * i + 1];
        }
#pragma unroll
        for (int o = 16; o; o >>= 1) sum += __shfl_xor_sync(~0u, sum, o);
        const float mean = sum * (1.0f / D);
        float var = 0.f;
#pragma unroll
        for (int i = 0; i < 14; i++) { const float d = xv[i] - mean; var += d * d; }
#pragma unroll
        for (int o = 16; o; o >>= 1) var += __shfl_xor_sync(~0u, var, o);
        const float mb = bf16r(mean);
        const float sd = bf16r(sqrtf(bf16r(bf16r(var * (1.0f / D)) + 1e-5f)));
        uint32_t* xn = reinterpret_cast<uint32_t*>(sm + OFF_XN + warp * XN_PITCH * 2);
#pragma unroll
        for (int i = 0; i < 7; i++) xn[lane + 32 * i] = pack_bf16(bf16r(xv[2 * i] - mb) / sd, bf16r(xv[2 * i + 1] - mb) / sd);
    }
    if (tid == 64) { sx->epoch[cta] = epoch + 1; s_tag[0] = epoch % 255u + 1u; s_tag[1] = epoch; }
    bar_sync(1, 256);
    const uint32_t tag = s_tag[0];
    float4* const acc_dst = &sx->acc[s_tag[1] & 1][b][warp * 24 + (lane >> 2) * 3 + (lane & 3)];

    auto project = [&](uint32_t wbase, int khalf, uint32_t bar, uint4* dst) {
        uint32_t xb[7][4];
#pragma unroll
        for (int i = 0; i < 7; i++) ldB(xb[i], sb + OFF_XN, XN_PITCH * 2, khalf * 224 + i * 32, zero, lane);
        float acc[2][4] = {};
        mbar_wait(bar, 0);
#pragma unroll
        for (int ks = 0; ks < 14; ks++) {
            const int row = ks * 16 + (lane & 7) + 8 * (lane >> 4);
            const int ch = 2 * (warp & 3) + ((lane >> 3) & 1);
            uint32_t a[4];
            ldsm4t(a, wbase + row * 128 + ((ch ^ (row & 7)) << 4));
            mma16816(acc[ks & 1], a, xb[ks >> 1][(ks & 1) * 2], xb[ks >> 1][(ks & 1) * 2 + 1]);
        }
        if ((lane & 3) == 0)
            pkt_store(dst + (warp & 3) * 8 + (lane >> 2), acc[0][0] + acc[1][0], acc[0][1] + acc[1][1], acc[0][2] + acc[1][2], acc[0][3] + acc[1][3], tag);
        __syncwarp();
        if (lane == 0) mbar_arrive(sb + BAR_WFREE, 1);
    };
    if (warp < 4) {
        project(sb + OFF_W, qblk & 1, sb + BAR_WQ, &sx->q[qblk * 32]);
    } else {
        if (!has_ffn && lane == 0) mbar_arrive(sb + BAR_WFREE, 1);
    }
    mbar_wait(sb + BAR_FULL + 2 * 8, 0);
    {
        const uint4* src = &sx->q[((grp & 7) * 8 + warp) * 64 + lane];
        uint4 u, v;
        int it = 0;
        do { u = pkt_load(src); v = pkt_load(src + 32); } while (((pkt_diff(u, tag) | pkt_diff(v, tag)) & 3u) && ++it < POLL_MAX);
        __nv_bfloat16* dst = reinterpret_cast<__nv_bfloat16*>(sm + OFF_Q) + warp * 64 + (lane >> 3) * 16 + (lane & 7);
        dst[0] = __float2bfloat16_rn(pkt_f(b ? u.y : u.x) + pkt_f(b ? v.y : v.x));
        dst[8] = __float2bfloat16_rn(pkt_f(b ? u.w : u.z) + pkt_f(b ? v.w : v.z));
    }
    bar_sync(1, 256);

    {
        const int g = lane >> 2, t4 = lane & 3;
        uint32_t qb[8][4];
#pragma unroll
        for (int i = 0; i < 8; i++) lds128(qb[i], sb + OFF_Q + (g & 1) * 512 + ((i ^ ((g >> 1) & 1)) * 32 + t4 * 8) * 2);
        const int mt = warp & 1;
        const uint32_t roff = (mt * 16 + 2 * g) * 512 + t4 * 16;
        for (int t = 0; t < NT; t++) {
            const int slot = t % NS;
            if ((slot & 3) != (warp >> 1)) continue;
            if (t >= GUT && t < GUT + 4 && warp >= 4 && has_ffn) project(sb + OFF_W + 28672, (fblk >> 1) & 1, sb + BAR_GU, &sx->h[fblk * 32]);
            mbar_wait(sb + BAR_FULL + slot * 8, (t / NS) & 1);
            const uint32_t base = sb + OFF_RING + slot * SLOT + roff;
            float acc0[4] = {}, acc1[4] = {};
#pragma unroll
            for (int i = 0; i < 8; i++) {
                uint32_t r0[4], r1[4];
                const uint32_t a = base + ((i ^ (g & 1)) << 6);
                lds128(r0, a);
                lds128(r1, a + 512);
                mma16816(acc0, r0[0], r1[0], r0[1], r1[1], qb[i][0], qb[i][1]);
                mma16816(acc1, r0[2], r1[2], r0[3], r1[3], qb[i][2], qb[i][3]);
            }
            __syncwarp();
            if (lane == 0) mbar_arrive(sb + BAR_EMPTY + slot * 8, 4);
            const float s0 = bf16r(acc0[0] + acc1[0]) * 0.0625f, s1 = bf16r(acc0[2] + acc1[2]) * 0.0625f;
            const float s2 = bf16r(acc0[1] + acc1[1]) * 0.0625f, s3 = bf16r(acc0[3] + acc1[3]) * 0.0625f;
            if (t < NA) sts128_if(t4 == (g & 1), sb + OFF_SC + ((t * 2 + mt) * 8 + g) * 16, s0, s1, s2, s3);
            else if (t4 == (g & 1)) pkt_store(&sx->sc[grp * MB * 128 + (((t - NA) * 8 + j) * 2 + mt) * 8 + g], s0, s1, s2, s3, tag);
        }
    }

    static_assert(VDEPTH <= KDEPTH && MB % 2 == 0 && TSC < TSTAT && TSTAT < NA && TWO >= NA && TO >= NA && NS > MB, "pipeline shape");
    const int ocol = b * D + warp * 64 + (lane >> 2) + 24 * ((lane & 3) < 3 ? (lane & 3) : 0);
    const uint4* g_src = &sx->g[(b * 7 + warp) * 32 + lane];
    const uint4* o_src = &sx->o[(cta * 8 + (warp & 6)) * 16 + (warp & 1) * 8 + (lane >> 2)];
    float xq[3] = {};
    if (warp < 7) {
        const __nv_bfloat16* xp = prm.x + ocol;
        xq[0] = __bfloat162float(xp[0]); xq[1] = __bfloat162float(xp[8]); xq[2] = __bfloat162float(xp[(lane & 3) < 2 ? 16 : 0]);
    }
    unsigned short* out_dst = reinterpret_cast<unsigned short*>(prm.out + ocol);
    uint32_t part_st = sb + OFF_PART2 + ((warp >> 1) * 64 + (warp & 1) * 32 + lane) * 4, part_ld = sb + OFF_PART2 + lane * 8;
    uint32_t wo_addr[4];
#pragma unroll
    for (int mt = 0; mt < 4; mt++) {
        const int row = (lane & 7) + 8 * (lane >> 4);
        wo_addr[mt] = sb + OFF_W + warp * 8192 + row * 128 + (((2 * mt + ((lane >> 3) & 1)) ^ (row & 7)) << 4);
        PIN32(wo_addr[mt]);
    }
    PIN64(out_dst); PIN64(g_src); PIN64(o_src); PIN32(part_st); PIN32(part_ld);
    uint4 gv;
    float oacc[2][4] = {};
    uint32_t wa[4][4][4];
    const int chb = (lane >> 3) & 1;
    {
        const float L2E = 1.4426950408889634f;
        uint32_t* const p0 = reinterpret_cast<uint32_t*>(sm + OFF_P);
        uint32_t* const p1 = reinterpret_cast<uint32_t*>(sm + OFF_P + P_PITCH * 2);
        uint4* const o_dst = &sx->o[((grp * 8 + warp) * 8 + j) * 16 + (lane >> 2)];
        if ((lane & 3) == 0) { pkt_clear(o_dst); pkt_clear(o_dst + 8); }
        float m0, m1, f0 = 1.f, f1 = 1.f;
        bar_sync(1, 256);
        {
            constexpr int NP = NA / 2;
            float e[NP][4];
#pragma unroll
            for (int i = 0; i < NP; i++) {
                const float4 v = *reinterpret_cast<const float4*>(sm + OFF_SC + (i * 32 + lane) * 16);
                e[i][0] = v.x; e[i][1] = v.y; e[i][2] = v.z; e[i][3] = v.w;
            }
            m0 = fmaxf(e[0][0], e[0][1]); m1 = fmaxf(e[0][2], e[0][3]);
#pragma unroll
            for (int i = 1; i < NP; i++) { m0 = fmaxf(m0, fmaxf(e[i][0], e[i][1])); m1 = fmaxf(m1, fmaxf(e[i][2], e[i][3])); }
#pragma unroll
            for (int o = 16; o; o >>= 1) {
                m0 = fmaxf(m0, __shfl_xor_sync(~0u, m0, o));
                m1 = fmaxf(m1, __shfl_xor_sync(~0u, m1, o));
            }
            float l0 = 0.f, l1 = 0.f;
#pragma unroll
            for (int i = 0; i < NP; i++) {
                e[i][0] = exp2f((e[i][0] - m0) * L2E); e[i][1] = exp2f((e[i][1] - m0) * L2E);
                e[i][2] = exp2f((e[i][2] - m1) * L2E); e[i][3] = exp2f((e[i][3] - m1) * L2E);
                l0 += e[i][0] + e[i][1]; l1 += e[i][2] + e[i][3];
                if (i == warp) { p0[i * 32 + lane] = pack_bf16(e[i][0], e[i][1]); p1[i * 32 + lane] = pack_bf16(e[i][2], e[i][3]); }
            }
            if (warp == 7) {
#pragma unroll
                for (int o = 16; o; o >>= 1) {
                    l0 += __shfl_xor_sync(~0u, l0, o);
                    l1 += __shfl_xor_sync(~0u, l1, o);
                }
                if (lane == 0) pkt_store(&sx->ml[cta], m0, l0, m1, l1, tag);
            }
        }
        bar_sync(1, 256);
        constexpr int NB = MB / 2;
        const uint4* const sc_src = &sx->sc[grp * MB * 128 + tid];
        const uint4* const ml_src = &sx->ml[grp * 8 + (lane & 7)];
        uint4 sv[NB], mv;
        int slot = NT % NS, ph = (NT / NS) & 1;
        const int rowl = (lane & 7) + 8 * (lane >> 4);
        const uint32_t voff = (warp >> 1) * 4096 + rowl * 128;
        const uint32_t vch0 = (((warp & 1) * 4 + chb) ^ (rowl & 7)) << 4, vch1 = (((warp & 1) * 4 + 2 + chb) ^ (rowl & 7)) << 4;
#pragma unroll 1
        for (int t = 0; t < NA; t++) {
            if (t == TSC) {
#pragma unroll
                for (int i = 0; i < NB; i++) sv[i] = pkt_load(sc_src + i * 256);
                mv = pkt_load(ml_src);
            }
            if (t == TSTAT) {
                int it = 0;
                for (;;) {
                    uint32_t bad = pkt_diff(mv, tag);
#pragma unroll
                    for (int i = 0; i < NB; i++) bad |= pkt_diff(sv[i], tag);
                    if (!(bad & 3u) || ++it >= POLL_MAX) break;
#pragma unroll
                    for (int i = 0; i < NB; i++) sv[i] = pkt_load(sc_src + i * 256);
                    mv = pkt_load(ml_src);
                }
                float e[NB][4];
                float n0 = -INFINITY, n1 = -INFINITY, l0 = 0.f, l1 = 0.f;
#pragma unroll
                for (int i = 0; i < NB; i++) {
                    e[i][0] = pkt_f(sv[i].x); e[i][1] = pkt_f(sv[i].y); e[i][2] = pkt_f(sv[i].z); e[i][3] = pkt_f(sv[i].w);
                    n0 = fmaxf(n0, fmaxf(e[i][0], e[i][1])); n1 = fmaxf(n1, fmaxf(e[i][2], e[i][3]));
                }
#pragma unroll
                for (int o = 16; o; o >>= 1) {
                    n0 = fmaxf(n0, __shfl_xor_sync(~0u, n0, o));
                    n1 = fmaxf(n1, __shfl_xor_sync(~0u, n1, o));
                }
#pragma unroll
                for (int i = 0; i < NB; i++) {
                    e[i][0] = exp2f((e[i][0] - n0) * L2E); e[i][1] = exp2f((e[i][1] - n0) * L2E);
                    e[i][2] = exp2f((e[i][2] - n1) * L2E); e[i][3] = exp2f((e[i][3] - n1) * L2E);
                    l0 += e[i][0] + e[i][1]; l1 += e[i][2] + e[i][3];
                }
#pragma unroll
                for (int o = 16; o; o >>= 1) {
                    l0 += __shfl_xor_sync(~0u, l0, o);
                    l1 += __shfl_xor_sync(~0u, l1, o);
                }
                if (lane == 0) *reinterpret_cast<float4*>(s_red + warp * 4) = make_float4(n0, l0, n1, l1);
                bar_sync(1, 256);
                float4 st = *reinterpret_cast<const float4*>(s_red + (lane & 7) * 4);
                if (lane & 8) st = make_float4(pkt_f(mv.x), pkt_f(mv.y), pkt_f(mv.z), pkt_f(mv.w));
                float M0 = st.x, M1 = st.z;
#pragma unroll
                for (int o = 8; o; o >>= 1) {
                    M0 = fmaxf(M0, __shfl_xor_sync(~0u, M0, o));
                    M1 = fmaxf(M1, __shfl_xor_sync(~0u, M1, o));
                }
                float L0 = st.y * exp2f((st.x - M0) * L2E), L1 = st.w * exp2f((st.z - M1) * L2E);
#pragma unroll
                for (int o = 8; o; o >>= 1) {
                    L0 += __shfl_xor_sync(~0u, L0, o);
                    L1 += __shfl_xor_sync(~0u, L1, o);
                }
                const float c0 = exp2f((n0 - M0) * L2E) / L0, c1 = exp2f((n1 - M1) * L2E) / L1;
                f0 = exp2f((m0 - M0) * L2E) / L0; f1 = exp2f((m1 - M1) * L2E) / L1;
#pragma unroll
                for (int i = 0; i < NB; i++) {
                    p0[NA * 16 + i * 256 + tid] = pack_bf16(e[i][0] * c0, e[i][1] * c0);
                    p1[NA * 16 + i * 256 + tid] = pack_bf16(e[i][2] * c1, e[i][3] * c1);
                }
            }
            uint32_t pb[4];
            ldB(pb, sb + OFF_P, P_PITCH * 2, t * 32, zero, lane);
            mbar_wait(sb + BAR_FULL + slot * 8, ph);
            const uint32_t base = sb + OFF_RING + slot * SLOT + voff;
#pragma unroll
            for (int ks = 0; ks < 2; ks++) {
                uint32_t a0[4], a1[4];
                ldsm4t(a0, base + ks * 2048 + vch0);
                ldsm4t(a1, base + ks * 2048 + vch1);
                mma16816(oacc[0], a0, pb[ks * 2], pb[ks * 2 + 1]);
                mma16816(oacc[1], a1, pb[ks * 2], pb[ks * 2 + 1]);
            }
            __syncwarp();
            if (lane == 0) mbar_arrive(sb + BAR_EMPTY + slot * 8, 1);
            if (++slot == NS) { slot = 0; ph ^= 1; }
        }
        if ((lane & 3) == 0) {
            pkt_store(o_dst, oacc[0][0] * f0, oacc[0][1] * f1, oacc[0][2] * f0, oacc[0][3] * f1, tag);
            pkt_store(o_dst + 8, oacc[1][0] * f0, oacc[1][1] * f1, oacc[1][2] * f0, oacc[1][3] * f1, tag);
        }
        bar_sync(1, 256);
        float o0[4] = {}, o1[4] = {}, o2[4] = {}, o3[4] = {};
        uint4 oa, ob;
        const int row2 = (warp >> 1) * 64 + (lane & 7) + 8 * (lane >> 4);
        const uint32_t voff2 = row2 * 64 + (((2 * (warp & 1) + chb) ^ ((row2 >> 1) & 3)) << 4);
#pragma unroll
        for (int t = NA; t < NT; t++) {
            if (t == TO) { oa = pkt_load(o_src); ob = pkt_load(o_src + 16); }
            if (t == NT - 1) {
                int it = 0;
                while (((pkt_diff(oa, tag) | pkt_diff(ob, tag)) & 3u) && ++it < POLL_MAX) { oa = pkt_load(o_src); ob = pkt_load(o_src + 16); }
                o0[0] += pkt_f(oa.x); o0[1] += pkt_f(oa.y); o0[2] += pkt_f(oa.z); o0[3] += pkt_f(oa.w);
                o1[0] += pkt_f(ob.x); o1[1] += pkt_f(ob.y); o1[2] += pkt_f(ob.z); o1[3] += pkt_f(ob.w);
            }
            if (t == TWO && warp < 7) {
                gv = pkt_load(g_src);
            }
            if (t == TWO && warp < 6) {
                mbar_wait(sb + BAR_WO + warp * 8, 0);
#pragma unroll
                for (int ks = 0; ks < 4; ks++)
#pragma unroll
                    for (int mt = 0; mt < 4; mt++) ldsm4t(wa[mt][ks], wo_addr[mt] + ks * 2048);
            }
            uint32_t pb[2][4];
            ldB(pb[0], sb + OFF_P, P_PITCH * 2, NA * 32 + (t - NA) * 256 + (warp >> 1) * 64, zero, lane);
            ldB(pb[1], sb + OFF_P, P_PITCH * 2, NA * 32 + (t - NA) * 256 + (warp >> 1) * 64 + 32, zero, lane);
            mbar_wait(sb + BAR_FULL + ((NT + t) % NS) * 8, ((NT + t) / NS) & 1);
            const uint32_t base = sb + OFF_RING + ((NT + t) % NS) * SLOT + voff2;
            uint32_t a[4][4];
            ldsm4t(a[0], base); ldsm4t(a[1], base + 1024); ldsm4t(a[2], base + 2048); ldsm4t(a[3], base + 3072);
            mma16816(o0, a[0], pb[0][0], pb[0][1]);
            mma16816(o1, a[1], pb[0][2], pb[0][3]);
            mma16816(o2, a[2], pb[1][0], pb[1][1]);
            mma16816(o3, a[3], pb[1][2], pb[1][3]);
        }
        sts128_if((lane & 3) == 0, part_st, (o0[0] + o1[0]) + (o2[0] + o3[0]), (o0[1] + o1[1]) + (o2[1] + o3[1]),
                  (o0[2] + o1[2]) + (o2[2] + o3[2]), (o0[3] + o1[3]) + (o2[3] + o3[3]));
    }
    if (warp == 7) { bar_arrive(2, 256); return; }
    bar_sync(2, 256);
    const float2 v0 = lds64(part_ld), v1 = lds64(part_ld + 256), v2 = lds64(part_ld + 512), v3 = lds64(part_ld + 768);
    const uint32_t ow = pack_bf16((v0.x + v1.x) + (v2.x + v3.x), (v0.y + v1.y) + (v2.y + v3.y));
    if (warp == 6) {
        mbar_wait(sb + BAR_WO + warp * 8, 0);
#pragma unroll
        for (int ks = 0; ks < 4; ks++)
#pragma unroll
            for (int mt = 0; mt < 4; mt++) ldsm4t(wa[mt][ks], wo_addr[mt] + ks * 2048);
    }
    float acc[2][4][4] = {};
#pragma unroll
    for (int ks = 0; ks < 4; ks++) {
        const uint32_t b0 = __shfl_sync(~0u, ow, ks * 8 + (lane & 3));
        const uint32_t b1 = __shfl_sync(~0u, ow, ks * 8 + 4 + (lane & 3));
#pragma unroll
        for (int mt = 0; mt < 4; mt++) mma16816(acc[ks & 1][mt], wa[mt][ks], b0, b1);
    }
    const int t4 = lane & 3;
    float sum[8];
#pragma unroll
    for (int mt = 0; mt < 4; mt++) { sum[2 * mt] = acc[0][mt][0] + acc[1][mt][0]; sum[2 * mt + 1] = acc[0][mt][2] + acc[1][mt][2]; }
    const float a0 = fsel(t4 == 0, sum[0], fsel(t4 == 1, sum[3], sum[6]));
    const float a1 = fsel(t4 == 0, sum[1], fsel(t4 == 1, sum[4], sum[7]));
    const float a2 = fsel(t4 == 0, sum[2], fsel(t4 == 1, sum[5], 0.f));
    if (t4 < 3) {
        float o0, o1, o2, cnt;
        asm volatile("atom.relaxed.gpu.global.add.v4.f32 {%0,%1,%2,%3}, [%4], {%5,%6,%7,%8};"
                     : "=f"(o0), "=f"(o1), "=f"(o2), "=f"(cnt) : "l"(acc_dst), "f"(a0), "f"(a1), "f"(a2), "f"(1.0f) : "memory");
        if (cnt == 63.f) {
            int it = 0;
            while ((pkt_diff(gv, tag) & 3u) && ++it < POLL_MAX) gv = pkt_load(g_src);
            const uint32_t r01 = pack_bf16(xq[0] + bf16r(bf16r(o0 + a0) * pkt_f(gv.x)), xq[1] + bf16r(bf16r(o1 + a1) * pkt_f(gv.y)));
            const uint32_t r2 = pack_bf16(xq[2] + bf16r(bf16r(o2 + a2) * pkt_f(gv.z)), 0.f);
            asm volatile("st.global.u16 [%0], %1;" :: "l"(out_dst), "h"((unsigned short)r01) : "memory");
            asm volatile("st.global.u16 [%0+16], %1;" :: "l"(out_dst), "h"((unsigned short)(r01 >> 16)) : "memory");
            if (t4 < 2) asm volatile("st.global.u16 [%0+32], %1;" :: "l"(out_dst), "h"((unsigned short)r2) : "memory");
        }
    }
}

typedef CUresult (*EncodeFn)(CUtensorMap*, CUtensorMapDataType, cuuint32_t, void*, const cuuint64_t*, const cuuint64_t*,
                             const cuuint32_t*, const cuuint32_t*, CUtensorMapInterleave, CUtensorMapSwizzle,
                             CUtensorMapL2promotion, CUtensorMapFloatOOBfill);

void make_map(EncodeFn enc, CUtensorMap* m, const void* ptr, uint64_t cols, uint64_t rows, uint32_t bc, uint32_t br,
              CUtensorMapSwizzle sw) {
    cuuint64_t dims[2] = {cols, rows};
    cuuint64_t strides[1] = {cols * 2};
    cuuint32_t box[2] = {bc, br};
    cuuint32_t es[2] = {1, 1};
    enc(m, CU_TENSOR_MAP_DATA_TYPE_BFLOAT16, 2, const_cast<void*>(ptr), dims, strides, box, es,
        CU_TENSOR_MAP_INTERLEAVE_NONE, sw, CU_TENSOR_MAP_L2_PROMOTION_L2_128B, CU_TENSOR_MAP_FLOAT_OOB_FILL_NONE);
}

}

extern "C" void kernel_launch(void* const* d_in, const int* in_sizes, int n_in, void* d_out, int out_size) {
    (void)in_sizes; (void)n_in; (void)out_size;
    static EncodeFn enc = nullptr;
    static Scratch* scratch = nullptr;
    if (!enc) {
        void* fn = nullptr;
        cudaDriverEntryPointQueryResult qr;
        cudaGetDriverEntryPoint("cuTensorMapEncodeTiled", &fn, cudaEnableDefault, &qr);
        enc = (EncodeFn)fn;
        cudaGetSymbolAddress((void**)&scratch, g_scratch);
        cudaFuncSetAttribute(fused_decode_kernel, cudaFuncAttributeMaxDynamicSharedMemorySize, SMEM_BYTES);
    }
    Params p;
    p.k = (const uint8_t*)d_in[1];
    p.wq_raw = (const uint8_t*)d_in[3];
    p.x = (const __nv_bfloat16*)d_in[0];
    p.out = (__nv_bfloat16*)d_out;
    p.sx = scratch;
    make_map(enc, &p.v,  d_in[2], 256,  (uint64_t)16 * SK, 32, 256, CU_TENSOR_MAP_SWIZZLE_64B);
    {
        cuuint64_t dims[3] = {64, (cuuint64_t)16 * SK, 4};
        cuuint64_t strides[2] = {512, 128};
        cuuint32_t box[3] = {64, 32, 4};
        cuuint32_t es[3] = {1, 1, 1};
        enc(&p.va, CU_TENSOR_MAP_DATA_TYPE_BFLOAT16, 3, d_in[2], dims, strides, box, es, CU_TENSOR_MAP_INTERLEAVE_NONE,
            CU_TENSOR_MAP_SWIZZLE_128B, CU_TENSOR_MAP_L2_PROMOTION_NONE, CU_TENSOR_MAP_FLOAT_OOB_FILL_NONE);
    }
    make_map(enc, &p.wq, d_in[3], 4096, D,  64, 224, CU_TENSOR_MAP_SWIZZLE_128B);
    {
        cuuint64_t dims[5] = {D, 16, 2, 8, 16};
        cuuint64_t strides[4] = {256 * D * 2, 8 * D * 2, D * 2, 16 * D * 2};
        cuuint32_t box[5] = {64, 2, 2, 8, 2};
        cuuint32_t es[5] = {1, 1, 1, 1, 1};
        enc(&p.wo, CU_TENSOR_MAP_DATA_TYPE_BFLOAT16, 5, d_in[4], dims, strides, box, es, CU_TENSOR_MAP_INTERLEAVE_NONE,
            CU_TENSOR_MAP_SWIZZLE_128B, CU_TENSOR_MAP_L2_PROMOTION_L2_128B, CU_TENSOR_MAP_FLOAT_OOB_FILL_NONE);
    }
    make_map(enc, &p.wg, d_in[6], FF,   D,  64, 224, CU_TENSOR_MAP_SWIZZLE_128B);
    make_map(enc, &p.wu, d_in[7], FF,   D,  64, 224, CU_TENSOR_MAP_SWIZZLE_128B);
    make_map(enc, &p.wd, d_in[8], D,    FF, 64, 128, CU_TENSOR_MAP_SWIZZLE_128B);
    fused_decode_kernel<<<NCTA, NTHREADS, SMEM_BYTES, cudaStreamPerThread>>>(p);
}
```

```cpp
#include <cuda_runtime.h>
#include <cuda_bf16.h>
#include <cuda.h>
#include <stdint.h>

namespace {

constexpr int D = 448, SK = 32768, WIN = 4096, FF = 1792;
constexpr int NMAIN = 128, NHELP = 4, NCTA = NMAIN + NHELP;
constexpr int NS = 9;
constexpr int SLOT = 16384;
constexpr int NT = 16;
constexpr int NTHREADS = 288;

constexpr int MB = 4, NA = NT - MB;
constexpr int KDEPTH = 3;
constexpr int VDEPTH = 2;
constexpr int NSTART = 2;
constexpr int GUPOS = 5;
constexpr int GUT = 6;
constexpr int WOPOS = 19;
constexpr int TSC = 7, TSTAT = 9;
constexpr int TWO = 13;
constexpr int TO = 14;

constexpr int tiles_in_window(int pair) {
    int c = 0;
    for (int t = GUT; t < GUT + 4; t++) c += ((t % NS) & 3) == pair;
    return c;
}
static_assert(tiles_in_window(2) == 1 && tiles_in_window(3) == 1 && GUPOS > NSTART && GUPOS <= GUT + NS - KDEPTH, "gate/up schedule");

constexpr int OFF_RING = 0;
constexpr int OFF_W    = OFF_RING + NS * SLOT;
constexpr int OFF_P    = OFF_W + 57344;
constexpr int P_PITCH  = NA * 32 + MB * 256 + 8;
constexpr int OFF_SC   = OFF_P + 2 * P_PITCH * 2;
constexpr int OFF_XN   = OFF_SC + NA * 256;
constexpr int XN_PITCH = 456;
constexpr int OFF_Q    = OFF_XN + 2 * XN_PITCH * 2;
constexpr int OFF_ZERO = OFF_Q + 1024;
constexpr int OFF_PART = OFF_ZERO + 16;
constexpr int OFF_PART2 = OFF_PART + 2048;
constexpr int OFF_RED  = OFF_PART2 + 1024;
constexpr int OFF_TAG  = OFF_RED + 128;
constexpr int OFF_BAR  = OFF_TAG + 16;
constexpr int BAR_FULL = OFF_BAR, BAR_EMPTY = BAR_FULL + NS * 8;
constexpr int BAR_WQ = BAR_EMPTY + NS * 8, BAR_GU = BAR_WQ + 8, BAR_WO = BAR_GU + 8, BAR_WFREE = BAR_WO + 7 * 8;
constexpr int SMEM_BYTES = BAR_WFREE + 8 + 1024;
constexpr int H_PITCH = FF + 8;
static_assert(OFF_XN % 16 == 0 && OFF_Q % 16 == 0 && OFF_P % 16 == 0 && OFF_PART % 16 == 0 && OFF_BAR % 8 == 0, "align");
static_assert(SMEM_BYTES <= 232448, "smem");

struct __align__(4096) Scratch {
    float4 acc[2][2][256];
    uint4 sc[16 * MB * 128];
    uint4 o[NMAIN * 8 * 16];
    uint4 ml[NMAIN];
    uint4 q[NMAIN * 32];
    uint4 h[112 * 32];
    uint4 g[2 * 7 * 32];
    unsigned epoch[NCTA];
};
__device__ Scratch g_scratch;

struct Params {
    const uint8_t* wq_raw;
    const uint8_t* k;
    const __nv_bfloat16* x;
    __nv_bfloat16* out;
    Scratch* sx;
    alignas(64) CUtensorMap wq;
    CUtensorMap v, va, wg, wu, wo, wd;
};

__device__ __forceinline__ uint32_t smem_u32(const void* p) { return (uint32_t)__cvta_generic_to_shared(p); }
__device__ __forceinline__ bool elect_one() {
    uint32_t p;
    asm volatile("{\n.reg .pred P;\nelect.sync _|P, 0xffffffff;\nselp.u32 %0, 1, 0, P;\n}" : "=r"(p));
    return p;
}
__device__ __forceinline__ void mbar_init(uint32_t bar, uint32_t cnt) {
    asm volatile("mbarrier.init.shared::cta.b64 [%0], %1;" :: "r"(bar), "r"(cnt) : "memory");
}
__device__ __forceinline__ void mbar_expect_tx(uint32_t bar, uint32_t bytes) {
    asm volatile("mbarrier.arrive.expect_tx.shared::cta.b64 _, [%0], %1;" :: "r"(bar), "r"(bytes) : "memory");
}
__device__ __forceinline__ void mbar_arrive(uint32_t bar, uint32_t cnt) {
    asm volatile("mbarrier.arrive.shared::cta.b64 _, [%0], %1;" :: "r"(bar), "r"(cnt) : "memory");
}
__device__ __forceinline__ void mbar_wait(uint32_t bar, uint32_t parity) {
    uint32_t ok;
    int it = 0;
    do {
        asm volatile("{\n.reg .pred p;\nmbarrier.test_wait.parity.shared::cta.b64 p, [%1], %2;\nselp.u32 %0, 1, 0, p;\n}"
                     : "=r"(ok) : "r"(bar), "r"(parity) : "memory");
    } while (!ok && ++it < (1 << 24));
}
__device__ __forceinline__ void bulk1d(uint32_t dst, const void* src, uint32_t bytes, uint32_t bar, uint64_t pol) {
    asm volatile("cp.async.bulk.shared::cluster.global.mbarrier::complete_tx::bytes.L2::cache_hint [%0], [%1], %2, [%3], %4;"
                 :: "r"(dst), "l"(src), "r"(bytes), "r"(bar), "l"(pol) : "memory");
}
__device__ __forceinline__ void tma2d(uint32_t dst, const CUtensorMap* map, int c0, int c1, uint32_t bar, uint64_t pol) {
    asm volatile("cp.async.bulk.tensor.2d.shared::cluster.global.mbarrier::complete_tx::bytes.L2::cache_hint [%0], [%1, {%3, %4}], [%2], %5;"
                 :: "r"(dst), "l"(map), "r"(bar), "r"(c0), "r"(c1), "l"(pol) : "memory");
}
__device__ __forceinline__ void tma3d(uint32_t dst, const CUtensorMap* map, int c1, uint32_t bar, uint64_t pol) {
    asm volatile("cp.async.bulk.tensor.3d.shared::cluster.global.mbarrier::complete_tx::bytes.L2::cache_hint [%0], [%1, {%4, %3, %4}], [%2], %5;"
                 :: "r"(dst), "l"(map), "r"(bar), "r"(c1), "r"(0), "l"(pol) : "memory");
}
__device__ __forceinline__ void tma5d(uint32_t dst, const CUtensorMap* map, int c0, int c1, int c4, uint32_t bar, uint64_t pol) {
    asm volatile("cp.async.bulk.tensor.5d.shared::cluster.global.mbarrier::complete_tx::bytes.L2::cache_hint [%0], [%1, {%3, %4, %6, %6, %5}], [%2], %7;"
                 :: "r"(dst), "l"(map), "r"(bar), "r"(c0), "r"(c1), "r"(c4), "r"(0), "l"(pol) : "memory");
}
__device__ __forceinline__ void ldsm4(uint32_t (&r)[4], uint32_t addr) {
    asm volatile("ldmatrix.sync.aligned.m8n8.x4.shared.b16 {%0,%1,%2,%3}, [%4];"
                 : "=r"(r[0]), "=r"(r[1]), "=r"(r[2]), "=r"(r[3]) : "r"(addr) : "memory");
}
__device__ __forceinline__ void ldsm4t(uint32_t (&r)[4], uint32_t addr) {
    asm volatile("ldmatrix.sync.aligned.m8n8.x4.trans.shared.b16 {%0,%1,%2,%3}, [%4];"
                 : "=r"(r[0]), "=r"(r[1]), "=r"(r[2]), "=r"(r[3]) : "r"(addr) : "memory");
}
__device__ __forceinline__ void lds128(uint32_t (&r)[4], uint32_t addr) {
    asm volatile("ld.shared.v4.u32 {%0,%1,%2,%3}, [%4];"
                 : "=r"(r[0]), "=r"(r[1]), "=r"(r[2]), "=r"(r[3]) : "r"(addr) : "memory");
}
__device__ __forceinline__ void sts128_if(bool c, uint32_t addr, float x, float y, float z, float w) {
    asm volatile("{\n.reg .pred p;\nsetp.ne.u32 p, %5, 0;\n@p st.shared.v4.f32 [%0], {%1,%2,%3,%4};\n}"
                 :: "r"(addr), "f"(x), "f"(y), "f"(z), "f"(w), "r"((uint32_t)c) : "memory");
}
__device__ __forceinline__ float2 lds64(uint32_t addr) {
    float2 v;
    asm volatile("ld.shared.v2.f32 {%0,%1}, [%2];" : "=f"(v.x), "=f"(v.y) : "r"(addr) : "memory");
    return v;
}
#define PIN32(x) asm volatile("" : "+r"(x))
#define PIN64(x) asm volatile("" : "+l"(x))
__device__ __forceinline__ void mma16816(float (&c)[4], uint32_t a0, uint32_t a1, uint32_t a2, uint32_t a3, uint32_t b0, uint32_t b1) {
    asm volatile("mma.sync.aligned.m16n8k16.row.col.f32.bf16.bf16.f32 {%0,%1,%2,%3}, {%4,%5,%6,%7}, {%8,%9}, {%0,%1,%2,%3};"
                 : "+f"(c[0]), "+f"(c[1]), "+f"(c[2]), "+f"(c[3])
                 : "r"(a0), "r"(a1), "r"(a2), "r"(a3), "r"(b0), "r"(b1));
}
__device__ __forceinline__ void mma16816(float (&c)[4], const uint32_t (&a)[4], uint32_t b0, uint32_t b1) {
    mma16816(c, a[0], a[1], a[2], a[3], b0, b1);
}
__device__ __forceinline__ void bar_sync(int id, int n) { asm volatile("bar.sync %0, %1;" :: "r"(id), "r"(n) : "memory"); }
__device__ __forceinline__ void bar_arrive(int id, int n) { asm volatile("bar.arrive %0, %1;" :: "r"(id), "r"(n) : "memory"); }
__device__ __forceinline__ uint32_t pack_bf16(float lo, float hi) {
    uint32_t r;
    asm("cvt.rn.bf16x2.f32 %0, %1, %2;" : "=r"(r) : "f"(hi), "f"(lo));
    return r;
}
__device__ __forceinline__ float bf16r(float v) { return __uint_as_float(pack_bf16(0.f, v)); }

__device__ __forceinline__ float fsel(bool c, float a, float b) {
    float r;
    asm("{\n.reg .pred p;\nsetp.ne.u32 p, %3, 0;\nselp.f32 %0, %1, %2, p;\n}" : "=f"(r) : "f"(a), "f"(b), "r"((uint32_t)c));
    return r;
}

__device__ __forceinline__ __nv_bfloat16 geglu(float gate, float up) {
    const float ga = bf16r(gate);
    const float in = 0.7978845608028654f * (ga + 0.044715f * ga * ga * ga);
    return __float2bfloat16_rn(bf16r(0.5f * ga * (1.0f + tanhf(in))) * bf16r(up));
}

__device__ __forceinline__ void ldB(uint32_t (&r)[4], uint32_t base, int pitch_bytes, int k0, uint32_t zero, int lane) {
    const int n = lane & 7;
    ldsm4(r, n < 2 ? base + n * pitch_bytes + (k0 + 8 * (lane >> 3)) * 2 : zero);
}

__device__ __forceinline__ void pkt_store(uint4* p, float a, float b, float c, float d, uint32_t tag) {
    const uint32_t w0 = (__float_as_uint(a) & ~3u) | (tag & 3u);
    const uint32_t w1 = (__float_as_uint(b) & ~3u) | ((tag >> 2) & 3u);
    const uint32_t w2 = (__float_as_uint(c) & ~3u) | ((tag >> 4) & 3u);
    const uint32_t w3 = (__float_as_uint(d) & ~3u) | ((tag >> 6) & 3u);
    asm volatile("{\n.reg .b128 t;\n.reg .b64 lo, hi;\nmov.b64 lo, {%1, %2};\nmov.b64 hi, {%3, %4};\nmov.b128 t, {lo, hi};\n"
                 "st.relaxed.gpu.global.b128 [%0], t;\n}"
                 :: "l"(p), "r"(w0), "r"(w1), "r"(w2), "r"(w3) : "memory");
}
__device__ __forceinline__ void pkt_clear(uint4* p) { pkt_store(p, 0.f, 0.f, 0.f, 0.f, 0); }
__device__ __forceinline__ uint4 pkt_load(const uint4* p) {
    uint4 v;
    asm volatile("{\n.reg .b128 t;\n.reg .b64 lo, hi;\nld.relaxed.gpu.global.b128 t, [%4];\nmov.b128 {lo, hi}, t;\n"
                 "mov.b64 {%0, %1}, lo;\nmov.b64 {%2, %3}, hi;\n}"
                 : "=r"(v.x), "=r"(v.y), "=r"(v.z), "=r"(v.w) : "l"(p) : "memory");
    return v;
}
__device__ __forceinline__ uint32_t pkt_diff(const uint4& v, uint32_t tag) {
    return ((v.x ^ tag) | (v.y ^ (tag >> 2))) | ((v.z ^ (tag >> 4)) | (v.w ^ (tag >> 6)));
}
__device__ __forceinline__ float pkt_f(uint32_t w) { return __uint_as_float(w & ~3u); }
constexpr int POLL_MAX = 1 << 20;

__global__ void __launch_bounds__(NTHREADS, 1) fused_decode_kernel(const __grid_constant__ Params prm) {
    extern __shared__ uint8_t smem_raw[];
    const int cta = blockIdx.x;
    const int tid = threadIdx.x, lane = tid & 31;
    const bool is_main = cta < NMAIN;
    if (tid == 0 && is_main) {
        uint64_t pol;
        asm volatile("createpolicy.fractional.L2::evict_normal.b64 %0, 1.0;" : "=l"(pol));
        asm volatile("cp.async.bulk.prefetch.L2.global.L2::cache_hint [%0], %1, %2;"
                     :: "l"(prm.wq_raw + cta * 28672), "r"(28672), "l"(pol) : "memory");
    }
    const int warp = __shfl_sync(~0u, tid >> 5, 0);

    const uint32_t sb = (smem_u32(smem_raw) + 1023u) & ~1023u;
    const int grp = cta >> 3, j = cta & 7;
    const int b = grp >> 3;
    const bool has_ffn = is_main && j < 7;
    const int fblk = grp * 7 + j;
    const int qblk = (grp & 7) * 16 + b * 8 + j;
    const int ncg = is_main ? 0 : (cta - NMAIN < 3 ? 2 : 1);
    const int cg0 = (cta - NMAIN) * 2;
    Scratch* const sx = prm.sx;
    uint8_t* const sm = smem_raw + (sb - smem_u32(smem_raw));
    volatile uint32_t* const s_tag = reinterpret_cast<volatile uint32_t*>(sm + OFF_TAG);

    if (warp == 8 && elect_one()) {
        uint64_t pol, npol;
        asm volatile("createpolicy.fractional.L2::evict_first.b64 %0, 1.0;" : "=l"(pol));
        asm volatile("createpolicy.fractional.L2::evict_normal.b64 %0, 1.0;" : "=l"(npol));
        const uint8_t* const ksrc = prm.k + (uint32_t)((grp * SK + (SK - WIN) + j * 32) * 512);
#pragma unroll
        for (int i = 0; i < NSTART; i++) mbar_init(sb + BAR_FULL + i * 8, 1);
        mbar_init(sb + BAR_WQ, 1);
        asm volatile("fence.mbarrier_init.release.cluster;" ::: "memory");
        if (is_main) {
            mbar_expect_tx(sb + BAR_WQ, 28672);
            tma2d(sb + OFF_W, &prm.wq, (qblk >> 1) * 64, (qblk & 1) * 224, sb + BAR_WQ, npol);
#pragma unroll
            for (int i = 0; i < NSTART; i++) {
                mbar_expect_tx(sb + BAR_FULL + i * 8, SLOT);
                bulk1d(sb + OFF_RING + i * SLOT, ksrc + (size_t)i * 256 * 512, SLOT, sb + BAR_FULL + i * 8, pol);
            }
        }
#pragma unroll
        for (int i = NSTART; i < NS; i++) mbar_init(sb + BAR_FULL + i * 8, 1);
#pragma unroll
        for (int i = 0; i < NS; i++) mbar_init(sb + BAR_EMPTY + i * 8, 8);
        mbar_init(sb + BAR_GU, 1); mbar_init(sb + BAR_WFREE, 8);
#pragma unroll
        for (int c = 0; c < 7; c++) mbar_init(sb + BAR_WO + c * 8, 1);
        asm volatile("fence.mbarrier_init.release.cluster;" ::: "memory");
    }

    const uint32_t zero = sb + OFF_ZERO;
    float* const s_part = reinterpret_cast<float*>(sm + OFF_PART);
    float* const s_red = reinterpret_cast<float*>(sm + OFF_RED);
    uint32_t xw[7];
    if (warp < 2 && is_main) {
        const uint32_t* xp = reinterpret_cast<const uint32_t*>(prm.x + warp * D);
#pragma unroll
        for (int i = 0; i < 7; i++) xw[i] = __ldg(xp + lane + 32 * i);
    }
    unsigned epoch = 0;
    if (tid == 64) epoch = sx->epoch[cta];
    if (tid == 96) *reinterpret_cast<uint4*>(sm + OFF_ZERO) = make_uint4(0, 0, 0, 0);
    if (is_main) {
        if (warp == 4) pkt_clear(&sx->q[qblk * 32 + lane]);
        if (warp == 5 && has_ffn) pkt_clear(&sx->h[fblk * 32 + lane]);
    } else if (warp < ncg * 2) {
        pkt_clear(&sx->g[((warp & 1) * 7 + cg0 + (warp >> 1)) * 32 + lane]);
    }
    __syncthreads();

    if (warp == 8) {
        const bool leader = elect_one();
        int ucta;
        asm volatile("mov.u32 %0, %%ctaid.x;" : "=r"(ucta));
        const uint8_t* const ksrc = prm.k + (uint32_t)(((ucta >> 3) * SK + (SK - WIN) + (ucta & 7) * 32) * 512);
        uint64_t pol, npol;
        asm volatile("createpolicy.fractional.L2::evict_first.b64 %0, 1.0;" : "=l"(pol));
        asm volatile("createpolicy.fractional.L2::evict_normal.b64 %0, 1.0;" : "=l"(npol));
        if (is_main) {
            if (leader) {
                asm volatile("prefetch.tensormap [%0];" :: "l"((fblk & 1) ? &prm.wu : &prm.wg) : "memory");
                asm volatile("prefetch.tensormap [%0];" :: "l"(&prm.va) : "memory");
                asm volatile("prefetch.tensormap [%0];" :: "l"(&prm.v) : "memory");
                asm volatile("prefetch.tensormap [%0];" :: "l"(&prm.wo) : "memory");
            }
            const int vrow = (ucta >> 3) * SK + (SK - WIN), vcol = (ucta & 7) * 32, wohead = ((ucta >> 3) & 7) * 2, woblk = (ucta & 7) * 2;
            uint32_t so = NSTART * 8, eph = 1, lo = 0, lph = 0;
            auto acquire = [&](int n) {
                if (n >= NS) mbar_wait(sb + BAR_EMPTY + so, eph);
                if (leader) mbar_expect_tx(sb + BAR_FULL + so, SLOT);
            };
            auto landing = [&]() {
                mbar_wait(sb + BAR_FULL + lo, lph);
            };
            auto advance = [&](bool l) {
                so += 8; if (so == NS * 8) { so = 0; eph ^= 1; }
                if (l) { lo += 8; if (lo == NS * 8) { lo = 0; lph ^= 1; } }
            };
            acquire(NSTART);
            mbar_wait(sb + BAR_WQ, 0);
            if (leader) bulk1d(sb + OFF_RING + so * (SLOT / 8), ksrc + NSTART * 256 * 512, SLOT, sb + BAR_FULL + so, pol);
            advance(false);
            const uint8_t* src = ksrc + (NSTART + 1) * 256 * 512;
#pragma unroll 1
            for (int n = NSTART + 1; n < NT; n++) {
                acquire(n);
                const uint32_t bar = sb + BAR_FULL + so, dst = sb + OFF_RING + so * (SLOT / 8);
                landing();
                if (leader) bulk1d(dst, src, SLOT, bar, pol);
                if (n == GUPOS && has_ffn && leader) {
                    mbar_expect_tx(sb + BAR_GU, 28672);
                    tma2d(sb + OFF_W + 28672, (fblk & 1) ? &prm.wu : &prm.wg, (fblk >> 2) * 64, ((fblk >> 1) & 1) * 224, sb + BAR_GU, npol);
                }
                src += 256 * 512;
                advance(true);
            }
            int row = vrow + vcol;
#pragma unroll 1
            for (int n = NT; n < NT + NA; n++) {
                acquire(n);
                if (n == WOPOS) mbar_wait(sb + BAR_WFREE, 0);
                const uint32_t bar = sb + BAR_FULL + so, dst = sb + OFF_RING + so * (SLOT / 8);
                landing();
                if (leader) tma3d(dst, &prm.va, row, bar, pol);
                if (n >= WOPOS && n < WOPOS + 6 && leader) {
                    const int c = n - WOPOS;
                    mbar_expect_tx(sb + BAR_WO + c * 8, 8192);
                    tma5d(sb + OFF_W + c * 8192, &prm.wo, c * 64, wohead, woblk, sb + BAR_WO + c * 8, npol);
                }
                row += 256;
                advance(true);
            }
            static_assert(KDEPTH == NSTART + 1 && VDEPTH == KDEPTH - 1 && WOPOS >= NT && WOPOS + 7 <= NT + NA, "producer loops");
            row = vrow + NA * 256;
            landing();
            lo += 8; if (lo == NS * 8) { lo = 0; lph ^= 1; }
#pragma unroll 1
            for (int n = NT + NA; n < 2 * NT; n++) {
                acquire(n);
                const uint32_t bar = sb + BAR_FULL + so, dst = sb + OFF_RING + so * (SLOT / 8);
                landing();
                if (leader) tma2d(dst, &prm.v, vcol, row, bar, pol);
                row += 256;
                advance(true);
            }
            if (leader) mbar_expect_tx(sb + BAR_WO + 6 * 8, 8192);
            landing();
            if (leader) tma5d(sb + OFF_W + 6 * 8192, &prm.wo, 6 * 64, wohead, woblk, sb + BAR_WO + 6 * 8, npol);
        } else {
            int slot = 0, ph = 1;
            for (int n = 0; n < 14 * ncg; n++) {
                if (n >= NS) mbar_wait(sb + BAR_EMPTY + slot * 8, ph);
                if (leader) {
                    mbar_expect_tx(sb + BAR_FULL + slot * 8, SLOT);
                    tma2d(sb + OFF_RING + slot * SLOT, &prm.wd, (cg0 + (ncg == 2 ? (n & 1) : 0)) * 64, (ncg == 2 ? (n >> 1) : n) * 128,
                          sb + BAR_FULL + slot * 8, npol);
                }
                if (++slot == NS) { slot = 0; ph ^= 1; }
            }
        }
        return;
    }

    if (!is_main) {
        if (tid == 64) { sx->epoch[cta] = epoch + 1; s_tag[0] = epoch % 255u + 1u; s_tag[1] = epoch; }
        bar_sync(1, 256);
        const uint32_t tag = s_tag[0];
        if (warp < 3) {
            const int i = (cta - NMAIN) * 3 + warp;
            sx->acc[(s_tag[1] + 1) & 1][i / 6][(i % 6) * 32 + lane] = make_float4(0.f, 0.f, 0.f, 0.f);
        }
        __nv_bfloat16* h_s = reinterpret_cast<__nv_bfloat16*>(sm + OFF_W);
        {
            uint4 v[4][4];
            const int ncb = warp < 4 ? 4 : 3;
            int it = 0;
            uint32_t bad;
            do {
                if (it) __nanosleep(200);
                bad = 0;
#pragma unroll
                for (int i = 0; i < 4; i++)
#pragma unroll
                    for (int q = 0; q < 4; q++)
                        if (i < ncb) v[i][q] = pkt_load(&sx->h[(warp + 8 * i) * 128 + q * 32 + lane]);
#pragma unroll
                for (int i = 0; i < 4; i++)
                    if (i < ncb) bad |= (pkt_diff(v[i][0], tag) | pkt_diff(v[i][1], tag)) | (pkt_diff(v[i][2], tag) | pkt_diff(v[i][3], tag));
            } while ((bad & 3u) && ++it < POLL_MAX);
#pragma unroll
            for (int i = 0; i < 4; i++) {
                if (i < ncb) {
                    __nv_bfloat16* dst = h_s + (warp + 8 * i) * 64 + (lane >> 3) * 16 + (lane & 7);
                    dst[0]           = geglu(pkt_f(v[i][0].x) + pkt_f(v[i][2].x), pkt_f(v[i][1].x) + pkt_f(v[i][3].x));
                    dst[H_PITCH]     = geglu(pkt_f(v[i][0].y) + pkt_f(v[i][2].y), pkt_f(v[i][1].y) + pkt_f(v[i][3].y));
                    dst[8]           = geglu(pkt_f(v[i][0].z) + pkt_f(v[i][2].z), pkt_f(v[i][1].z) + pkt_f(v[i][3].z));
                    dst[H_PITCH + 8] = geglu(pkt_f(v[i][0].w) + pkt_f(v[i][2].w), pkt_f(v[i][1].w) + pkt_f(v[i][3].w));
                }
            }
        }
        bar_sync(1, 256);
        const int mt = warp & 3, kh = warp >> 2;
        float acc[2][4] = {};
        int slot = 0, ph = 0;
        for (int rb = 0; rb < 14; rb++) {
            uint32_t bf[2][4];
            ldB(bf[0], sb + OFF_W, H_PITCH * 2, rb * 128 + kh * 64, zero, lane);
            ldB(bf[1], sb + OFF_W, H_PITCH * 2, rb * 128 + kh * 64 + 32, zero, lane);
#pragma unroll
            for (int ci = 0; ci < 2; ci++) {
                if (ci < ncg) {
                    mbar_wait(sb + BAR_FULL + slot * 8, ph);
                    const uint32_t base = sb + OFF_RING + slot * SLOT;
#pragma unroll
                    for (int ks = 0; ks < 4; ks++) {
                        const int row = kh * 64 + ks * 16 + (lane & 7) + 8 * (lane >> 4);
                        const int ch = 2 * mt + ((lane >> 3) & 1);
                        uint32_t a[4];
                        ldsm4t(a, base + row * 128 + ((ch ^ (row & 7)) << 4));
                        mma16816(acc[ci], a, bf[ks >> 1][(ks & 1) * 2], bf[ks >> 1][(ks & 1) * 2 + 1]);
                    }
                    __syncwarp();
                    if (lane == 0) mbar_arrive(sb + BAR_EMPTY + slot * 8, 1);
                    if (++slot == NS) { slot = 0; ph ^= 1; }
                }
            }
        }
        if ((lane & 3) == 0) {
#pragma unroll
            for (int ci = 0; ci < 2; ci++) {
                float* p = s_part + kh * 256 + ci * 128 + (mt * 16 + (lane >> 2)) * 2;
                p[0] = acc[ci][0]; p[1] = acc[ci][1]; p[16] = acc[ci][2]; p[17] = acc[ci][3];
            }
        }
        bar_sync(1, 256);
        if (warp < ncg * 2) {
            const int ci = warp >> 1, bb = warp & 1;
            float g[3];
#pragma unroll
            for (int i = 0; i < 3; i++) {
                const int col = ((lane >> 2) + 8 * (3 * (lane & 3) + i)) & 63;
                const float y = bf16r(s_part[ci * 128 + col * 2 + bb] + s_part[256 + ci * 128 + col * 2 + bb]);
                g[i] = bf16r(y / (1.0f + expf(-y)));
            }
            pkt_store(&sx->g[(bb * 7 + cg0 + ci) * 32 + lane], g[0], g[1], g[2], 0.f, tag);
        }
        return;
    }

    if (warp < 2) {
        float xv[14], sum = 0.f;
#pragma unroll
        for (int i = 0; i < 7; i++) {
            xv[2 * i] = __uint_as_float(xw[i] << 16);
            xv[2 * i + 1] = __uint_as_float(xw[i] & 0xffff0000u);
            sum += xv[2 * i] + xv[2 * i + 1];
        }
#pragma unroll
        for (int o = 16; o; o >>= 1) sum += __shfl_xor_sync(~0u, sum, o);
        const float mean = sum * (1.0f / D);
        float var = 0.f;
#pragma unroll
        for (int i = 0; i < 14; i++) { const float d = xv[i] - mean; var += d * d; }
#pragma unroll
        for (int o = 16; o; o >>= 1) var += __shfl_xor_sync(~0u, var, o);
        const float mb = bf16r(mean);
        const float sd = bf16r(sqrtf(bf16r(bf16r(var * (1.0f / D)) + 1e-5f)));
        uint32_t* xn = reinterpret_cast<uint32_t*>(sm + OFF_XN + warp * XN_PITCH * 2);
#pragma unroll
        for (int i = 0; i < 7; i++) xn[lane + 32 * i] = pack_bf16(bf16r(xv[2 * i] - mb) / sd, bf16r(xv[2 * i + 1] - mb) / sd);
    }
    if (tid == 64) { sx->epoch[cta] = epoch + 1; s_tag[0] = epoch % 255u + 1u; s_tag[1] = epoch; }
    bar_sync(1, 256);
    const uint32_t tag = s_tag[0];
    float4* const acc_dst = &sx->acc[s_tag[1] & 1][b][warp * 24 + (lane >> 2) * 3 + (lane & 3)];

    auto project = [&](uint32_t wbase, int khalf, uint32_t bar, uint4* dst) {
        uint32_t xb[7][4];
#pragma unroll
        for (int i = 0; i < 7; i++) ldB(xb[i], sb + OFF_XN, XN_PITCH * 2, khalf * 224 + i * 32, zero, lane);
        float acc[2][4] = {};
        mbar_wait(bar, 0);
#pragma unroll
        for (int ks = 0; ks < 14; ks++) {
            const int row = ks * 16 + (lane & 7) + 8 * (lane >> 4);
            const int ch = 2 * (warp & 3) + ((lane >> 3) & 1);
            uint32_t a[4];
            ldsm4t(a, wbase + row * 128 + ((ch ^ (row & 7)) << 4));
            mma16816(acc[ks & 1], a, xb[ks >> 1][(ks & 1) * 2], xb[ks >> 1][(ks & 1) * 2 + 1]);
        }
        if ((lane & 3) == 0)
            pkt_store(dst + (warp & 3) * 8 + (lane >> 2), acc[0][0] + acc[1][0], acc[0][1] + acc[1][1], acc[0][2] + acc[1][2], acc[0][3] + acc[1][3], tag);
        __syncwarp();
        if (lane == 0) mbar_arrive(sb + BAR_WFREE, 1);
    };
    if (warp < 4) {
        project(sb + OFF_W, qblk & 1, sb + BAR_WQ, &sx->q[qblk * 32]);
    } else {
        if (!has_ffn && lane == 0) mbar_arrive(sb + BAR_WFREE, 1);
    }
    mbar_wait(sb + BAR_FULL + 2 * 8, 0);
    {
        const uint4* src = &sx->q[((grp & 7) * 8 + warp) * 64 + lane];
        uint4 u, v;
        int it = 0;
        do { u = pkt_load(src); v = pkt_load(src + 32); } while (((pkt_diff(u, tag) | pkt_diff(v, tag)) & 3u) && ++it < POLL_MAX);
        __nv_bfloat16* dst = reinterpret_cast<__nv_bfloat16*>(sm + OFF_Q) + warp * 64 + (lane >> 3) * 16 + (lane & 7);
        dst[0] = __float2bfloat16_rn(pkt_f(b ? u.y : u.x) + pkt_f(b ? v.y : v.x));
        dst[8] = __float2bfloat16_rn(pkt_f(b ? u.w : u.z) + pkt_f(b ? v.w : v.z));
    }
    bar_sync(1, 256);

    {
        const int g = lane >> 2, t4 = lane & 3;
        uint32_t qb[8][4];
#pragma unroll
        for (int i = 0; i < 8; i++) lds128(qb[i], sb + OFF_Q + (g & 1) * 512 + ((i ^ ((g >> 1) & 1)) * 32 + t4 * 8) * 2);
        const int mt = warp & 1;
        const uint32_t roff = (mt * 16 + 2 * g) * 512 + t4 * 16;
        for (int t = 0; t < NT; t++) {
            const int slot = t % NS;
            if ((slot & 3) != (warp >> 1)) continue;
            if (t >= GUT && t < GUT + 4 && warp >= 4 && has_ffn) project(sb + OFF_W + 28672, (fblk >> 1) & 1, sb + BAR_GU, &sx->h[fblk * 32]);
            mbar_wait(sb + BAR_FULL + slot * 8, (t / NS) & 1);
            const uint32_t base = sb + OFF_RING + slot * SLOT + roff;
            float acc0[4] = {}, acc1[4] = {};
#pragma unroll
            for (int i = 0; i < 8; i++) {
                uint32_t r0[4], r1[4];
                const uint32_t a = base + ((i ^ (g & 1)) << 6);
                lds128(r0, a);
                lds128(r1, a + 512);
                mma16816(acc0, r0[0], r1[0], r0[1], r1[1], qb[i][0], qb[i][1]);
                mma16816(acc1, r0[2], r1[2], r0[3], r1[3], qb[i][2], qb[i][3]);
            }
            __syncwarp();
            if (lane == 0) mbar_arrive(sb + BAR_EMPTY + slot * 8, 4);
            const float s0 = bf16r(acc0[0] + acc1[0]) * 0.0625f, s1 = bf16r(acc0[2] + acc1[2]) * 0.0625f;
            const float s2 = bf16r(acc0[1] + acc1[1]) * 0.0625f, s3 = bf16r(acc0[3] + acc1[3]) * 0.0625f;
            if (t < NA) sts128_if(t4 == (g & 1), sb + OFF_SC + ((t * 2 + mt) * 8 + g) * 16, s0, s1, s2, s3);
            else if (t4 == (g & 1)) pkt_store(&sx->sc[grp * MB * 128 + (((t - NA) * 8 + j) * 2 + mt) * 8 + g], s0, s1, s2, s3, tag);
        }
    }

    static_assert(VDEPTH <= KDEPTH && MB % 2 == 0 && TSC < TSTAT && TSTAT < NA && TWO >= NA && TO >= NA && NS > MB, "pipeline shape");
    const int ocol = b * D + warp * 64 + (lane >> 2) + 24 * ((lane & 3) < 3 ? (lane & 3) : 0);
    const uint4* g_src = &sx->g[(b * 7 + warp) * 32 + lane];
    const uint4* o_src = &sx->o[(cta * 8 + (warp & 6)) * 16 + (warp & 1) * 8 + (lane >> 2)];
    float xq[3] = {};
    if (warp < 7) {
        const __nv_bfloat16* xp = prm.x + ocol;
        xq[0] = __bfloat162float(xp[0]); xq[1] = __bfloat162float(xp[8]); xq[2] = __bfloat162float(xp[(lane & 3) < 2 ? 16 : 0]);
    }
    unsigned short* out_dst = reinterpret_cast<unsigned short*>(prm.out + ocol);
    uint32_t part_st = sb + OFF_PART2 + ((warp >> 1) * 64 + (warp & 1) * 32 + lane) * 4, part_ld = sb + OFF_PART2 + lane * 8;
    uint32_t wo_addr[4];
#pragma unroll
    for (int mt = 0; mt < 4; mt++) {
        const int row = (lane & 7) + 8 * (lane >> 4);
        wo_addr[mt] = sb + OFF_W + warp * 8192 + row * 128 + (((2 * mt + ((lane >> 3) & 1)) ^ (row & 7)) << 4);
        PIN32(wo_addr[mt]);
    }
    PIN64(out_dst); PIN64(g_src); PIN64(o_src); PIN32(part_st); PIN32(part_ld);
    uint4 gv;
    float oacc[2][4] = {};
    uint32_t wa[4][4][4];
    const int chb = (lane >> 3) & 1;
    {
        const float L2E = 1.4426950408889634f;
        uint32_t* const p0 = reinterpret_cast<uint32_t*>(sm + OFF_P);
        uint32_t* const p1 = reinterpret_cast<uint32_t*>(sm + OFF_P + P_PITCH * 2);
        uint4* const o_dst = &sx->o[((grp * 8 + warp) * 8 + j) * 16 + (lane >> 2)];
        if ((lane & 3) == 0) { pkt_clear(o_dst); pkt_clear(o_dst + 8); }
        float m0, m1, f0 = 1.f, f1 = 1.f;
        bar_sync(1, 256);
        {
            constexpr int NP = NA / 2;
            float e[NP][4];
#pragma unroll
            for (int i = 0; i < NP; i++) {
                const float4 v = *reinterpret_cast<const float4*>(sm + OFF_SC + (i * 32 + lane) * 16);
                e[i][0] = v.x; e[i][1] = v.y; e[i][2] = v.z; e[i][3] = v.w;
            }
            m0 = fmaxf(e[0][0], e[0][1]); m1 = fmaxf(e[0][2], e[0][3]);
#pragma unroll
            for (int i = 1; i < NP; i++) { m0 = fmaxf(m0, fmaxf(e[i][0], e[i][1])); m1 = fmaxf(m1, fmaxf(e[i][2], e[i][3])); }
#pragma unroll
            for (int o = 16; o; o >>= 1) {
                m0 = fmaxf(m0, __shfl_xor_sync(~0u, m0, o));
                m1 = fmaxf(m1, __shfl_xor_sync(~0u, m1, o));
            }
            float l0 = 0.f, l1 = 0.f;
#pragma unroll
            for (int i = 0; i < NP; i++) {
                e[i][0] = exp2f((e[i][0] - m0) * L2E); e[i][1] = exp2f((e[i][1] - m0) * L2E);
                e[i][2] = exp2f((e[i][2] - m1) * L2E); e[i][3] = exp2f((e[i][3] - m1) * L2E);
                l0 += e[i][0] + e[i][1]; l1 += e[i][2] + e[i][3];
                if (i == warp) { p0[i * 32 + lane] = pack_bf16(e[i][0], e[i][1]); p1[i * 32 + lane] = pack_bf16(e[i][2], e[i][3]); }
            }
            if (warp == 7) {
#pragma unroll
                for (int o = 16; o; o >>= 1) {
                    l0 += __shfl_xor_sync(~0u, l0, o);
                    l1 += __shfl_xor_sync(~0u, l1, o);
                }
                if (lane == 0) pkt_store(&sx->ml[cta], m0, l0, m1, l1, tag);
            }
        }
        bar_sync(1, 256);
        constexpr int NB = MB / 2;
        const uint4* const sc_src = &sx->sc[grp * MB * 128 + tid];
        const uint4* const ml_src = &sx->ml[grp * 8 + (lane & 7)];
        uint4 sv[NB], mv;
        int slot = NT % NS, ph = (NT / NS) & 1;
        const int rowl = (lane & 7) + 8 * (lane >> 4);
        const uint32_t voff = (warp >> 1) * 4096 + rowl * 128;
        const uint32_t vch0 = (((warp & 1) * 4 + chb) ^ (rowl & 7)) << 4, vch1 = (((warp & 1) * 4 + 2 + chb) ^ (rowl & 7)) << 4;
#pragma unroll 1
        for (int t = 0; t < NA; t++) {
            if (t == TSC) {
#pragma unroll
                for (int i = 0; i < NB; i++) sv[i] = pkt_load(sc_src + i * 256);
                mv = pkt_load(ml_src);
            }
            if (t == TSTAT) {
                int it = 0;
                for (;;) {
                    uint32_t bad = pkt_diff(mv, tag);
#pragma unroll
                    for (int i = 0; i < NB; i++) bad |= pkt_diff(sv[i], tag);
                    if (!(bad & 3u) || ++it >= POLL_MAX) break;
#pragma unroll
                    for (int i = 0; i < NB; i++) sv[i] = pkt_load(sc_src + i * 256);
                    mv = pkt_load(ml_src);
                }
                float e[NB][4];
                float n0 = -INFINITY, n1 = -INFINITY, l0 = 0.f, l1 = 0.f;
#pragma unroll
                for (int i = 0; i < NB; i++) {
                    e[i][0] = pkt_f(sv[i].x); e[i][1] = pkt_f(sv[i].y); e[i][2] = pkt_f(sv[i].z); e[i][3] = pkt_f(sv[i].w);
                    n0 = fmaxf(n0, fmaxf(e[i][0], e[i][1])); n1 = fmaxf(n1, fmaxf(e[i][2], e[i][3]));
                }
#pragma unroll
                for (int o = 16; o; o >>= 1) {
                    n0 = fmaxf(n0, __shfl_xor_sync(~0u, n0, o));
                    n1 = fmaxf(n1, __shfl_xor_sync(~0u, n1, o));
                }
#pragma unroll
                for (int i = 0; i < NB; i++) {
                    e[i][0] = exp2f((e[i][0] - n0) * L2E); e[i][1] = exp2f((e[i][1] - n0) * L2E);
                    e[i][2] = exp2f((e[i][2] - n1) * L2E); e[i][3] = exp2f((e[i][3] - n1) * L2E);
                    l0 += e[i][0] + e[i][1]; l1 += e[i][2] + e[i][3];
                }
#pragma unroll
                for (int o = 16; o; o >>= 1) {
                    l0 += __shfl_xor_sync(~0u, l0, o);
                    l1 += __shfl_xor_sync(~0u, l1, o);
                }
                if (lane == 0) *reinterpret_cast<float4*>(s_red + warp * 4) = make_float4(n0, l0, n1, l1);
                bar_sync(1, 256);
                float4 st = *reinterpret_cast<const float4*>(s_red + (lane & 7) * 4);
                if (lane & 8) st = make_float4(pkt_f(mv.x), pkt_f(mv.y), pkt_f(mv.z), pkt_f(mv.w));
                float M0 = st.x, M1 = st.z;
#pragma unroll
                for (int o = 8; o; o >>= 1) {
                    M0 = fmaxf(M0, __shfl_xor_sync(~0u, M0, o));
                    M1 = fmaxf(M1, __shfl_xor_sync(~0u, M1, o));
                }
                float L0 = st.y * exp2f((st.x - M0) * L2E), L1 = st.w * exp2f((st.z - M1) * L2E);
#pragma unroll
                for (int o = 8; o; o >>= 1) {
                    L0 += __shfl_xor_sync(~0u, L0, o);
                    L1 += __shfl_xor_sync(~0u, L1, o);
                }
                const float c0 = exp2f((n0 - M0) * L2E) / L0, c1 = exp2f((n1 - M1) * L2E) / L1;
                f0 = exp2f((m0 - M0) * L2E) / L0; f1 = exp2f((m1 - M1) * L2E) / L1;
#pragma unroll
                for (int i = 0; i < NB; i++) {
                    p0[NA * 16 + i * 256 + tid] = pack_bf16(e[i][0] * c0, e[i][1] * c0);
                    p1[NA * 16 + i * 256 + tid] = pack_bf16(e[i][2] * c1, e[i][3] * c1);
                }
            }
            uint32_t pb[4];
            ldB(pb, sb + OFF_P, P_PITCH * 2, t * 32, zero, lane);
            mbar_wait(sb + BAR_FULL + slot * 8, ph);
            const uint32_t base = sb + OFF_RING + slot * SLOT + voff;
#pragma unroll
            for (int ks = 0; ks < 2; ks++) {
                uint32_t a0[4], a1[4];
                ldsm4t(a0, base + ks * 2048 + vch0);
                ldsm4t(a1, base + ks * 2048 + vch1);
                mma16816(oacc[0], a0, pb[ks * 2], pb[ks * 2 + 1]);
                mma16816(oacc[1], a1, pb[ks * 2], pb[ks * 2 + 1]);
            }
            __syncwarp();
            if (lane == 0) mbar_arrive(sb + BAR_EMPTY + slot * 8, 1);
            if (++slot == NS) { slot = 0; ph ^= 1; }
        }
        if ((lane & 3) == 0) {
            pkt_store(o_dst, oacc[0][0] * f0, oacc[0][1] * f1, oacc[0][2] * f0, oacc[0][3] * f1, tag);
            pkt_store(o_dst + 8, oacc[1][0] * f0, oacc[1][1] * f1, oacc[1][2] * f0, oacc[1][3] * f1, tag);
        }
        bar_sync(1, 256);
        float o0[4] = {}, o1[4] = {}, o2[4] = {}, o3[4] = {};
        uint4 oa, ob;
        const int row2 = (warp >> 1) * 64 + (lane & 7) + 8 * (lane >> 4);
        const uint32_t voff2 = row2 * 64 + (((2 * (warp & 1) + chb) ^ ((row2 >> 1) & 3)) << 4);
#pragma unroll
        for (int t = NA; t < NT; t++) {
            if (t == TO) { oa = pkt_load(o_src); ob = pkt_load(o_src + 16); }
            if (t == NT - 1) {
                int it = 0;
                while (((pkt_diff(oa, tag) | pkt_diff(ob, tag)) & 3u) && ++it < POLL_MAX) { oa = pkt_load(o_src); ob = pkt_load(o_src + 16); }
                o0[0] += pkt_f(oa.x); o0[1] += pkt_f(oa.y); o0[2] += pkt_f(oa.z); o0[3] += pkt_f(oa.w);
                o1[0] += pkt_f(ob.x); o1[1] += pkt_f(ob.y); o1[2] += pkt_f(ob.z); o1[3] += pkt_f(ob.w);
            }
            if (t == TWO && warp < 7) {
                gv = pkt_load(g_src);
            }
            if (t == TWO && warp < 6) {
                mbar_wait(sb + BAR_WO + warp * 8, 0);
#pragma unroll
                for (int ks = 0; ks < 4; ks++)
#pragma unroll
                    for (int mt = 0; mt < 4; mt++) ldsm4t(wa[mt][ks], wo_addr[mt] + ks * 2048);
            }
            uint32_t pb[2][4];
            ldB(pb[0], sb + OFF_P, P_PITCH * 2, NA * 32 + (t - NA) * 256 + (warp >> 1) * 64, zero, lane);
            ldB(pb[1], sb + OFF_P, P_PITCH * 2, NA * 32 + (t - NA) * 256 + (warp >> 1) * 64 + 32, zero, lane);
            mbar_wait(sb + BAR_FULL + ((NT + t) % NS) * 8, ((NT + t) / NS) & 1);
            const uint32_t base = sb + OFF_RING + ((NT + t) % NS) * SLOT + voff2;
            uint32_t a[4][4];
            ldsm4t(a[0], base); ldsm4t(a[1], base + 1024); ldsm4t(a[2], base + 2048); ldsm4t(a[3], base + 3072);
            mma16816(o0, a[0], pb[0][0], pb[0][1]);
            mma16816(o1, a[1], pb[0][2], pb[0][3]);
            mma16816(o2, a[2], pb[1][0], pb[1][1]);
            mma16816(o3, a[3], pb[1][2], pb[1][3]);
        }
        sts128_if((lane & 3) == 0, part_st, (o0[0] + o1[0]) + (o2[0] + o3[0]), (o0[1] + o1[1]) + (o2[1] + o3[1]),
                  (o0[2] + o1[2]) + (o2[2] + o3[2]), (o0[3] + o1[3]) + (o2[3] + o3[3]));
    }
    if (warp == 7) { bar_arrive(2, 256); return; }
    bar_sync(2, 256);
    const float2 v0 = lds64(part_ld), v1 = lds64(part_ld + 256), v2 = lds64(part_ld + 512), v3 = lds64(part_ld + 768);
    const uint32_t ow = pack_bf16((v0.x + v1.x) + (v2.x + v3.x), (v0.y + v1.y) + (v2.y + v3.y));
    if (warp == 6) {
        mbar_wait(sb + BAR_WO + warp * 8, 0);
#pragma unroll
        for (int ks = 0; ks < 4; ks++)
#pragma unroll
            for (int mt = 0; mt < 4; mt++) ldsm4t(wa[mt][ks], wo_addr[mt] + ks * 2048);
    }
    float acc[2][4][4] = {};
#pragma unroll
    for (int ks = 0; ks < 4; ks++) {
        const uint32_t b0 = __shfl_sync(~0u, ow, ks * 8 + (lane & 3));
        const uint32_t b1 = __shfl_sync(~0u, ow, ks * 8 + 4 + (lane & 3));
#pragma unroll
        for (int mt = 0; mt < 4; mt++) mma16816(acc[ks & 1][mt], wa[mt][ks], b0, b1);
    }
    const int t4 = lane & 3;
    float sum[8];
#pragma unroll
    for (int mt = 0; mt < 4; mt++) { sum[2 * mt] = acc[0][mt][0] + acc[1][mt][0]; sum[2 * mt + 1] = acc[0][mt][2] + acc[1][mt][2]; }
    const float a0 = fsel(t4 == 0, sum[0], fsel(t4 == 1, sum[3], sum[6]));
    const float a1 = fsel(t4 == 0, sum[1], fsel(t4 == 1, sum[4], sum[7]));
    const float a2 = fsel(t4 == 0, sum[2], fsel(t4 == 1, sum[5], 0.f));
    if (t4 < 3) {
        float o0, o1, o2, cnt;
        asm volatile("atom.relaxed.gpu.global.add.v4.f32 {%0,%1,%2,%3}, [%4], {%5,%6,%7,%8};"
                     : "=f"(o0), "=f"(o1), "=f"(o2), "=f"(cnt) : "l"(acc_dst), "f"(a0), "f"(a1), "f"(a2), "f"(1.0f) : "memory");
        if (cnt == 63.f) {
            int it = 0;
            while ((pkt_diff(gv, tag) & 3u) && ++it < POLL_MAX) gv = pkt_load(g_src);
            const uint32_t r01 = pack_bf16(xq[0] + bf16r(bf16r(o0 + a0) * pkt_f(gv.x)), xq[1] + bf16r(bf16r(o1 + a1) * pkt_f(gv.y)));
            const uint32_t r2 = pack_bf16(xq[2] + bf16r(bf16r(o2 + a2) * pkt_f(gv.z)), 0.f);
            asm volatile("st.global.u16 [%0], %1;" :: "l"(out_dst), "h"((unsigned short)r01) : "memory");
            asm volatile("st.global.u16 [%0+16], %1;" :: "l"(out_dst), "h"((unsigned short)(r01 >> 16)) : "memory");
            if (t4 < 2) asm volatile("st.global.u16 [%0+32], %1;" :: "l"(out_dst), "h"((unsigned short)r2) : "memory");
        }
    }
}

typedef CUresult (*EncodeFn)(CUtensorMap*, CUtensorMapDataType, cuuint32_t, void*, const cuuint64_t*, const cuuint64_t*,
                             const cuuint32_t*, const cuuint32_t*, CUtensorMapInterleave, CUtensorMapSwizzle,
                             CUtensorMapL2promotion, CUtensorMapFloatOOBfill);

void make_map(EncodeFn enc, CUtensorMap* m, const void* ptr, uint64_t cols, uint64_t rows, uint32_t bc, uint32_t br,
              CUtensorMapSwizzle sw) {
    cuuint64_t dims[2] = {cols, rows};
    cuuint64_t strides[1] = {cols * 2};
    cuuint32_t box[2] = {bc, br};
    cuuint32_t es[2] = {1, 1};
    enc(m, CU_TENSOR_MAP_DATA_TYPE_BFLOAT16, 2, const_cast<void*>(ptr), dims, strides, box, es,
        CU_TENSOR_MAP_INTERLEAVE_NONE, sw, CU_TENSOR_MAP_L2_PROMOTION_L2_128B, CU_TENSOR_MAP_FLOAT_OOB_FILL_NONE);
}

}

extern "C" void kernel_launch(void* const* d_in, const int* in_sizes, int n_in, void* d_out, int out_size) {
    (void)in_sizes; (void)n_in; (void)out_size;
    static EncodeFn enc = nullptr;
    static Scratch* scratch = nullptr;
    if (!enc) {
        void* fn = nullptr;
        cudaDriverEntryPointQueryResult qr;
        cudaGetDriverEntryPoint("cuTensorMapEncodeTiled", &fn, cudaEnableDefault, &qr);
        enc = (EncodeFn)fn;
        cudaGetSymbolAddress((void**)&scratch, g_scratch);
        cudaFuncSetAttribute(fused_decode_kernel, cudaFuncAttributeMaxDynamicSharedMemorySize, SMEM_BYTES);
    }
    Params p;
    p.k = (const uint8_t*)d_in[1];
    p.wq_raw = (const uint8_t*)d_in[3];
    p.x = (const __nv_bfloat16*)d_in[0];
    p.out = (__nv_bfloat16*)d_out;
    p.sx = scratch;
    make_map(enc, &p.v,  d_in[2], 256,  (uint64_t)16 * SK, 32, 256, CU_TENSOR_MAP_SWIZZLE_64B);
    {
        cuuint64_t dims[3] = {64, (cuuint64_t)16 * SK, 4};
        cuuint64_t strides[2] = {512, 128};
        cuuint32_t box[3] = {64, 32, 4};
        cuuint32_t es[3] = {1, 1, 1};
        enc(&p.va, CU_TENSOR_MAP_DATA_TYPE_BFLOAT16, 3, d_in[2], dims, strides, box, es, CU_TENSOR_MAP_INTERLEAVE_NONE,
            CU_TENSOR_MAP_SWIZZLE_128B, CU_TENSOR_MAP_L2_PROMOTION_NONE, CU_TENSOR_MAP_FLOAT_OOB_FILL_NONE);
    }
    make_map(enc, &p.wq, d_in[3], 4096, D,  64, 224, CU_TENSOR_MAP_SWIZZLE_128B);
    {
        cuuint64_t dims[5] = {D, 16, 2, 8, 16};
        cuuint64_t strides[4] = {256 * D * 2, 8 * D * 2, D * 2, 16 * D * 2};
        cuuint32_t box[5] = {64, 2, 2, 8, 2};
        cuuint32_t es[5] = {1, 1, 1, 1, 1};
        enc(&p.wo, CU_TENSOR_MAP_DATA_TYPE_BFLOAT16, 5, d_in[4], dims, strides, box, es, CU_TENSOR_MAP_INTERLEAVE_NONE,
            CU_TENSOR_MAP_SWIZZLE_128B, CU_TENSOR_MAP_L2_PROMOTION_L2_128B, CU_TENSOR_MAP_FLOAT_OOB_FILL_NONE);
    }
    make_map(enc, &p.wg, d_in[6], FF,   D,  64, 224, CU_TENSOR_MAP_SWIZZLE_128B);
    make_map(enc, &p.wu, d_in[7], FF,   D,  64, 224, CU_TENSOR_MAP_SWIZZLE_128B);
    make_map(enc, &p.wd, d_in[8], D,    FF, 64, 128, CU_TENSOR_MAP_SWIZZLE_128B);
    fused_decode_kernel<<<NCTA, NTHREADS, SMEM_BYTES, cudaStreamPerThread>>>(p);
}
```
